```python
import torch

def _softmax(x, axis=-1):
    return torch.softmax(x, dim=axis)
def _gelu(x):
    return torch.nn.functional.gelu(x, approximate="tanh")
def _silu(x):
    return torch.nn.functional.silu(x)
def _sigmoid(x):
    return torch.sigmoid(x)
def _layernorm(x, axis=-1, eps=1e-5):
    m = x.mean(dim=axis, keepdim=True)
    v = x.var(dim=axis, keepdim=True, unbiased=False)
    return (x - m) / torch.sqrt(v + eps)
def _scatter_add(tgt, idx, src, axis=0):
    return tgt.clone().index_add_(axis, idx, src)
def _segment_sum(src, seg, n):
    out = torch.zeros((n,) + src.shape[1:], dtype=src.dtype)
    return out.index_add_(0, seg, src)
def _pad(x, pw):
    flat = tuple(v for pair in reversed(pw) for v in pair)
    return torch.nn.functional.pad(x, flat)

kernel_name = 'concat_heads__ssm_conv_s5__mha_block__prompt'

def setup_inputs():

    _w = (lambda a: (lambda t: t.to(torch.bfloat16) if t.is_floating_point() else t)(torch.as_tensor(a)))
    def _A_setup():
        B, S, D = 1, 2048, 576
        P = D
        Lambda_re = -0.5 * (lambda _x: torch.exp(torch.as_tensor(_x)))((lambda *s: torch.randn(*s, dtype=torch.bfloat16) * 0.4)(P))
        Lambda_im = (lambda *s: torch.randn(*s, dtype=torch.bfloat16) * 0.8)(P) * 1.0
        B_re = (lambda *s: torch.randn(*s, dtype=torch.bfloat16) * 0.8)(P, D) * (D ** -0.5)
        B_im = (lambda *s: torch.randn(*s, dtype=torch.bfloat16) * 0.8)(P, D) * (D ** -0.5)
        C_re = (lambda *s: torch.randn(*s, dtype=torch.bfloat16) * 0.8)(D, P) * (P ** -0.5)
        C_im = (lambda *s: torch.randn(*s, dtype=torch.bfloat16) * 0.8)(D, P) * (P ** -0.5)
        log_dt = (lambda *s: torch.randn(*s, dtype=torch.bfloat16) * 0.4)(P) * 0.3 - 2.0
        Dskip = (lambda *s: torch.randn(*s, dtype=torch.bfloat16) * 0.1)(D)
        return {
            "x": _w((lambda *s: torch.randn(*s, dtype=torch.bfloat16) * 0.05)(B, S, D)),
            "Lambda_re": _w(Lambda_re),
            "Lambda_im": _w(Lambda_im),
            "B_re": _w(B_re),
            "B_im": _w(B_im),
            "C_re": _w(C_re),
            "C_im": _w(C_im),
            "log_dt": _w(log_dt),
            "Dskip": _w(Dskip),
        }
    _A_in = _A_setup()

    def _B_setup():
        B, S, D, H = 1, 2048, 576, 32
        return {
            "x": _w((lambda *s: torch.randn(*s, dtype=torch.bfloat16) * 0.2)(B, S, D)),
            "wqkv": _w((lambda *s: torch.randn(*s, dtype=torch.bfloat16) * 0.2)(D, 3 * D)),
            "wo": _w((lambda *s: torch.randn(*s, dtype=torch.bfloat16) * 0.05)(D, D)),
        }
    _B_in = _B_setup()

    return {
        "A_x": _A_in["x"],
        "A_Lambda_re": _A_in["Lambda_re"],
        "A_Lambda_im": _A_in["Lambda_im"],
        "A_B_re": _A_in["B_re"],
        "A_B_im": _A_in["B_im"],
        "A_C_re": _A_in["C_re"],
        "A_C_im": _A_in["C_im"],
        "A_log_dt": _A_in["log_dt"],
        "A_Dskip": _A_in["Dskip"],
        "B_x": _B_in["x"],
        "B_wqkv": _B_in["wqkv"],
        "B_wo": _B_in["wo"],
    }

def reference(A_x, A_Lambda_re, A_Lambda_im, A_B_re, A_B_im, A_C_re, A_C_im, A_log_dt, A_Dskip, B_x, B_wqkv, B_wo):
    def _A_ref(x, Lambda_re, Lambda_im, B_re, B_im, C_re, C_im, log_dt, Dskip):
        Bsz, L, H = x.shape
        Lam = Lambda_re + 1j * Lambda_im
        Bmat = B_re + 1j * B_im
        Cmat = C_re + 1j * C_im
        dt = torch.exp(log_dt)
        Lam_bar = torch.exp(dt * Lam)
        B_bar = ((Lam_bar - 1.0) / Lam)[:, None] * Bmat
        Bu = torch.einsum("bld,pd->blp", x + 0j, B_bar)
        h = torch.zeros_like(Bu[:, 0, :])
        hs = []
        for t in range(L):
            h = Lam_bar[None, :] * h + Bu[:, t, :]
            hs.append(h)
        hseq = torch.stack(hs, 1)
        y = 2.0 * torch.einsum("blp,dp->bld", hseq, Cmat).real + x * Dskip[None, None, :]
        return y

    def _B_ref(x, wqkv, wo):
        B, S, D = x.shape
        H = 32
        Dh = D // H
        qkv = (lambda x, *d: x.permute(*d))((x @ wqkv).reshape(B, S, 3, H, Dh), 2, 0, 3, 1, 4)
        q, k, v = qkv[0], qkv[1], qkv[2]
        scores = torch.einsum("bhqd,bhkd->bhqk", q, k) * (Dh ** -0.5)
        p = _softmax(scores, axis=-1)
        o = torch.einsum("bhqk,bhkd->bhqd", p, v)
        return (lambda x, *d: x.permute(*d))(o, 0, 2, 1, 3).reshape(B, S, D) @ wo

    a = _A_ref(A_x, A_Lambda_re, A_Lambda_im, A_B_re, A_B_im, A_C_re, A_C_im, A_log_dt, A_Dskip)
    b = _B_ref(B_x, B_wqkv, B_wo)
    return torch.concatenate([a, b], axis=-1)
```

```cpp
#include <cuda_runtime.h>
#include <cuda.h>
#include <cuda_bf16.h>
#include <cuda_fp16.h>
#include <stdint.h>

namespace {

__device__ __align__(1024) uint8_t g_q[32 * 65536];
__device__ __align__(1024) uint8_t g_kv[32 * 131072];
__device__ __align__(1024) uint32_t g_t[96 * 2048];
__device__ __align__(1024) uint8_t g_o[32 * 73728];
__device__ __align__(1024) uint8_t g_w[8 * 82944];
__device__ __align__(1024) uint8_t g_h[1152 * 4096];
__device__ uint2 g_kn[32 * 128];
__device__ uint2 g_vm[4 * 128];
__device__ float4 g_agg[12 * 576];
constexpr int C_DONE = 0, C_QKV = 1, C_H = 25, C_O = 38, C_W = 54;
__device__ uint32_t g_cnt[55 * 64];

__device__ __forceinline__ uint32_t smem_u32(const void* p) { return (uint32_t)__cvta_generic_to_shared(p); }
__device__ __forceinline__ void wfence() { asm volatile("wgmma.fence.sync.aligned;" ::: "memory"); }
__device__ __forceinline__ void wcommit() { asm volatile("wgmma.commit_group.sync.aligned;" ::: "memory"); }
template <int N> __device__ __forceinline__ void wwait() { asm volatile("wgmma.wait_group.sync.aligned %0;" ::"n"(N) : "memory"); }
template <int N> __device__ __forceinline__ void fence_regs(float (&d)[N]) {
#pragma unroll
  for (int i = 0; i < N; i++) asm volatile("" : "+f"(d[i])::"memory");
}
template <int N> __device__ __forceinline__ void fence_regs(uint32_t (&d)[N]) {
#pragma unroll
  for (int i = 0; i < N; i++) asm volatile("" : "+r"(d[i])::"memory");
}
__device__ __forceinline__ uint64_t mkdesc(uint32_t lo, uint32_t hi) { uint64_t d; asm("mov.b64 %0, {%1, %2};" : "=l"(d) : "r"(lo), "r"(hi)); return d; }
__device__ __forceinline__ void mbar_init(uint32_t a, int c) { asm volatile("mbarrier.init.shared::cta.b64 [%0], %1;" ::"r"(a), "r"(c)); }
__device__ __forceinline__ void mbar_init_fence() { asm volatile("fence.mbarrier_init.release.cluster;" ::: "memory"); }
__device__ __forceinline__ void mbar_expect(uint32_t a, uint32_t b) { asm volatile("mbarrier.arrive.expect_tx.shared::cta.b64 _, [%0], %1;" ::"r"(a), "r"(b) : "memory"); }
__device__ __forceinline__ void mbar_arrive(uint32_t a) { asm volatile("mbarrier.arrive.shared::cta.b64 _, [%0];" ::"r"(a) : "memory"); }
__device__ __forceinline__ void mbar_wait(uint32_t a, uint32_t ph) {
  asm volatile("{\n.reg .pred p;\n.reg .u32 n;\nmov.u32 n, 0;\nW:\nmbarrier.try_wait.parity.shared::cta.b64 p, [%0], %1;\n@p bra.uni E;\n"
               "add.u32 n, n, 1;\nsetp.lt.u32 p, n, 4194304;\n@p bra.uni W;\ntrap;\nE:\n}\n" ::"r"(a), "r"(ph) : "memory");
}
__device__ __forceinline__ void bulk_g2s(uint32_t dst, const void* src, uint32_t bytes, uint32_t mbar) {
  asm volatile("cp.async.bulk.shared::cluster.global.mbarrier::complete_tx::bytes [%0], [%1], %2, [%3];" ::"r"(dst), "l"(src), "r"(bytes), "r"(mbar) : "memory");
}
__device__ __forceinline__ void bulk_commit() { asm volatile("cp.async.bulk.commit_group;" ::: "memory"); }
__device__ __forceinline__ void bulk_wait0() { asm volatile("cp.async.bulk.wait_group 0;" ::: "memory"); }
__device__ __forceinline__ void tma2d(uint32_t dst, const CUtensorMap* m, int c0, int c1, uint32_t mbar) {
  asm volatile("cp.async.bulk.tensor.2d.shared::cluster.global.mbarrier::complete_tx::bytes [%0], [%1, {%3, %4}], [%2];" ::"r"(dst), "l"(m), "r"(mbar), "r"(c0), "r"(c1) : "memory");
}
__device__ __forceinline__ void tma3d(uint32_t dst, const CUtensorMap* m, int c0, int c1, int c2, uint32_t mbar) {
  asm volatile("cp.async.bulk.tensor.3d.shared::cluster.global.mbarrier::complete_tx::bytes [%0], [%1, {%3, %4, %5}], [%2];" ::"r"(dst), "l"(m), "r"(mbar), "r"(c0), "r"(c1), "r"(c2) : "memory");
}
__device__ __forceinline__ void tma5d(uint32_t dst, const CUtensorMap* m, int c0, int c4, uint32_t mbar) {
  asm volatile("cp.async.bulk.tensor.5d.shared::cluster.global.mbarrier::complete_tx::bytes [%0], [%1, {%3, %5, %5, %5, %4}], [%2];" ::"r"(dst), "l"(m), "r"(mbar), "r"(c0), "r"(c4), "r"(0) : "memory");
}
__device__ __forceinline__ void tma3d_store(const CUtensorMap* m, uint32_t src, int c0, int c1, int c2) {
  asm volatile("cp.async.bulk.tensor.3d.global.shared::cta.bulk_group [%0, {%2, %3, %4}], [%1];" ::"l"(m), "r"(src), "r"(c0), "r"(c1), "r"(c2) : "memory");
}
__device__ __forceinline__ void tmap_prefetch(const CUtensorMap* m) { asm volatile("prefetch.tensormap [%0];" ::"l"(m) : "memory"); }
__device__ __forceinline__ void fence_async() { asm volatile("fence.proxy.async.shared::cta;" ::: "memory"); }
__device__ __forceinline__ void bar_sync(int id, int n) { asm volatile("bar.sync %0, %1;" ::"r"(id), "r"(n) : "memory"); }
__device__ __forceinline__ float ex2(float x) { float y; asm("ex2.approx.ftz.f32 %0, %1;" : "=f"(y) : "f"(x)); return y; }
__device__ __forceinline__ uint32_t packbf(float lo, float hi) { uint32_t r; asm("cvt.rn.bf16x2.f32 %0, %1, %2;" : "=r"(r) : "f"(hi), "f"(lo)); return r; }
__device__ __forceinline__ uint32_t packh(float lo, float hi) { uint32_t r; asm("cvt.rn.f16x2.f32 %0, %1, %2;" : "=r"(r) : "f"(hi), "f"(lo)); return r; }
__device__ __forceinline__ void sts32(uint32_t a, uint32_t v) { asm volatile("st.shared.b32 [%0], %1;" ::"r"(a), "r"(v) : "memory"); }
__device__ __forceinline__ void sts64(uint32_t a, uint32_t x, uint32_t y) { asm volatile("st.shared.v2.b32 [%0], {%1, %2};" ::"r"(a), "r"(x), "r"(y) : "memory"); }
__device__ __forceinline__ void sts128(uint32_t a, uint32_t x, uint32_t y, uint32_t z, uint32_t w) { asm volatile("st.shared.v4.b32 [%0], {%1, %2, %3, %4};" ::"r"(a), "r"(x), "r"(y), "r"(z), "r"(w) : "memory"); }
__device__ __forceinline__ uint4 lds128(uint32_t a) { uint4 v; asm volatile("ld.shared.v4.b32 {%0, %1, %2, %3}, [%4];" : "=r"(v.x), "=r"(v.y), "=r"(v.z), "=r"(v.w) : "r"(a) : "memory"); return v; }
__device__ __forceinline__ uint32_t lds32(uint32_t a) { uint32_t v; asm volatile("ld.shared.b32 %0, [%1];" : "=r"(v) : "r"(a) : "memory"); return v; }
__device__ __forceinline__ uint32_t hfma2(uint32_t a, uint32_t b, uint32_t c) { uint32_t r; asm("fma.rn.f16x2 %0, %1, %2, %3;" : "=r"(r) : "r"(a), "r"(b), "r"(c)); return r; }

__device__ __forceinline__ void tma2d_store(const CUtensorMap* m, uint32_t src, int c0, int c1) {
  asm volatile("cp.async.bulk.tensor.2d.global.shared::cta.bulk_group [%0, {%2, %3}], [%1];" ::"l"(m), "r"(src), "r"(c0), "r"(c1) : "memory");
}
__device__ __forceinline__ void fence_async_g() { asm volatile("fence.proxy.async.global;" ::: "memory"); }
__device__ __forceinline__ void red_relaxed(uint32_t* p, uint32_t v) { asm volatile("red.relaxed.gpu.global.add.u32 [%0], %1;" ::"l"(p), "r"(v) : "memory"); }
__device__ __forceinline__ void red_release(uint32_t* p, uint32_t v) { asm volatile("red.release.gpu.global.add.u32 [%0], %1;" ::"l"(p), "r"(v) : "memory"); }
__device__ __forceinline__ uint32_t ld_l2(const void* p) { uint32_t v; asm volatile("ld.relaxed.gpu.global.u32 %0, [%1];" : "=r"(v) : "l"(p) : "memory"); return v; }
__device__ __forceinline__ void wait_count(const uint32_t* p, uint32_t target) {
  for (uint32_t it = 0; __any_sync(0xffffffffu, (int32_t)(ld_l2(p) - target) < 0);)
    if (++it > (1u << 21)) __trap();
}
__device__ __forceinline__ bool bar_or(int id, int n, bool p) {
  uint32_t r;
  asm volatile("{\n.reg .pred p, q;\nsetp.ne.u32 p, %3, 0;\nbar.red.or.pred q, %1, %2, p;\nselp.u32 %0, 1, 0, q;\n}\n" : "=r"(r) : "r"(id), "r"(n), "r"((uint32_t)p) : "memory");
  return __any_sync(0xffffffffu, r);
}
__device__ __forceinline__ float2 h2f(uint32_t x) { return __half22float2(*(__half2*)&x); }
__device__ __forceinline__ void bar_arrive(int id, int n) { asm volatile("bar.arrive %0, %1;" ::"r"(id), "r"(n) : "memory"); }
__device__ __forceinline__ int tid_v() { int v; asm volatile("mov.u32 %0, %%tid.x;" : "=r"(v)); return v; }
__device__ __forceinline__ int bid_v() { int v; asm volatile("mov.u32 %0, %%ctaid.x;" : "=r"(v)); return v; }
__device__ __forceinline__ float4 ld_l2_f4(const void* p) { float4 v; asm volatile("ld.relaxed.gpu.global.v4.f32 {%0, %1, %2, %3}, [%4];" : "=f"(v.x), "=f"(v.y), "=f"(v.z), "=f"(v.w) : "l"(p) : "memory"); return v; }
__device__ __forceinline__ void tma4d(uint32_t dst, const CUtensorMap* m, int c0, int c1, int c2, int c3, uint32_t mbar) {
  asm volatile("cp.async.bulk.tensor.4d.shared::cluster.global.mbarrier::complete_tx::bytes [%0], [%1, {%3, %4, %5, %6}], [%2];" ::"r"(dst), "l"(m), "r"(mbar), "r"(c0), "r"(c1), "r"(c2), "r"(c3) : "memory");
}
__device__ __forceinline__ uint32_t hadd2(uint32_t a, uint32_t b) { uint32_t r; asm("add.rn.f16x2 %0, %1, %2;" : "=r"(r) : "r"(a), "r"(b)); return r; }
__device__ __forceinline__ uint2 lds64(uint32_t a) { uint2 v; asm volatile("ld.shared.v2.b32 {%0, %1}, [%2];" : "=r"(v.x), "=r"(v.y) : "r"(a) : "memory"); return v; }
__device__ __forceinline__ void stsm4(uint32_t a, uint32_t x, uint32_t y, uint32_t z, uint32_t w) {
  asm volatile("stmatrix.sync.aligned.m8n8.x4.shared.b16 [%0], {%1, %2, %3, %4};" ::"r"(a), "r"(x), "r"(y), "r"(z), "r"(w) : "memory");
}
__device__ __forceinline__ void st_tag(uint2* p, uint32_t v, uint32_t ep) { asm volatile("st.relaxed.gpu.global.v2.u32 [%0], {%1, %2};" ::"l"(p), "r"(v), "r"(ep) : "memory"); }
__device__ __forceinline__ uint4 ld_l2_u4(const void* p) { uint4 v; asm volatile("ld.relaxed.gpu.global.v4.u32 {%0, %1, %2, %3}, [%4];" : "=r"(v.x), "=r"(v.y), "=r"(v.z), "=r"(v.w) : "l"(p) : "memory"); return v; }
__device__ __forceinline__ void pf_line(const void* p) { asm volatile("prefetch.global.L2 [%0];" ::"l"(p)); }
template <class T> __device__ __forceinline__ void pin(T& x) { asm volatile("" : "+r"(x)); }
__device__ __forceinline__ void ldsm4(uint32_t (&r)[4], uint32_t a) {
  asm volatile("ldmatrix.sync.aligned.m8n8.x4.shared.b16 {%0, %1, %2, %3}, [%4];" : "=r"(r[0]), "=r"(r[1]), "=r"(r[2]), "=r"(r[3]) : "r"(a) : "memory");
}
__device__ __forceinline__ float sqrt_a(float x) { float y; asm("sqrt.approx.ftz.f32 %0, %1;" : "=f"(y) : "f"(x)); return y; }
__device__ __forceinline__ uint32_t max_tagged(const uint2* p, uint32_t ep) {
  uint32_t m;
  asm volatile("{\n.reg .pred p, q;\n.reg .u32 n, a, b, c, d, e, f, g, h;\nmov.u32 n, 0;\nW:\nld.relaxed.gpu.global.v4.u32 {a, b, c, d}, [%1];\n"
               "ld.relaxed.gpu.global.v4.u32 {e, f, g, h}, [%1 + 512];\nsetp.eq.u32 p, b, %2;\nsetp.eq.and.u32 p, d, %2, p;\n"
               "setp.eq.and.u32 p, f, %2, p;\nsetp.eq.and.u32 p, h, %2, p;\nvote.sync.all.pred q, p, 0xffffffff;\n@q bra.uni E;\n"
               "add.u32 n, n, 1;\nsetp.lt.u32 q, n, 2097152;\n@q bra.uni W;\ntrap;\nE:\nmax.u32 a, a, c;\nmax.u32 e, e, g;\nmax.u32 a, a, e;\n"
               "redux.sync.max.u32 %0, a, 0xffffffff;\n}\n"
               : "=r"(m) : "l"(p), "r"(ep) : "memory");
  return m;
}
__device__ __forceinline__ void bulk_wait_read() { asm volatile("cp.async.bulk.wait_group.read 0;" ::: "memory"); }
__device__ __forceinline__ void bulk_s2g(void* dst, uint32_t src, uint32_t bytes) {
  asm volatile("cp.async.bulk.global.shared::cta.bulk_group [%0], [%1], %2;" ::"l"(dst), "r"(src), "r"(bytes) : "memory");
}
__device__ __forceinline__ void rsb(float (&d)[36], uint32_t a0, uint32_t a1, uint32_t a2, uint32_t a3, uint64_t db, int sd) {
  asm volatile("{\n.reg .pred p;\nsetp.ne.b32 p, %41, 0;\n"
    "wgmma.mma_async.sync.aligned.m64n72k16.f32.bf16.bf16 "
    "{%0,%1,%2,%3,%4,%5,%6,%7,%8,%9,%10,%11,%12,%13,%14,%15,%16,%17,%18,%19,%20,%21,%22,%23,%24,%25,%26,%27,%28,%29,%30,%31,%32,%33,%34,%35},{%36,%37,%38,%39},%40,p,1,1,1;\n}\n"
    : "+f"(d[0]),"+f"(d[1]),"+f"(d[2]),"+f"(d[3]),"+f"(d[4]),"+f"(d[5]),"+f"(d[6]),"+f"(d[7]),"+f"(d[8]),"+f"(d[9]),"+f"(d[10]),"+f"(d[11]),"+f"(d[12]),"+f"(d[13]),"+f"(d[14]),"+f"(d[15]),"+f"(d[16]),"+f"(d[17]),"+f"(d[18]),"+f"(d[19]),"+f"(d[20]),"+f"(d[21]),"+f"(d[22]),"+f"(d[23]),"+f"(d[24]),"+f"(d[25]),"+f"(d[26]),"+f"(d[27]),"+f"(d[28]),"+f"(d[29]),"+f"(d[30]),"+f"(d[31]),"+f"(d[32]),"+f"(d[33]),"+f"(d[34]),"+f"(d[35])
    : "r"(a0), "r"(a1), "r"(a2), "r"(a3), "l"(db), "r"(sd));
}
__device__ __forceinline__ void rsb(float (&d)[8], uint32_t a0, uint32_t a1, uint32_t a2, uint32_t a3, uint64_t db, int sd) {
  asm volatile("{\n.reg .pred p;\nsetp.ne.b32 p, %13, 0;\n"
    "wgmma.mma_async.sync.aligned.m64n16k16.f32.bf16.bf16 "
    "{%0,%1,%2,%3,%4,%5,%6,%7},{%8,%9,%10,%11},%12,p,1,1,1;\n}\n"
    : "+f"(d[0]),"+f"(d[1]),"+f"(d[2]),"+f"(d[3]),"+f"(d[4]),"+f"(d[5]),"+f"(d[6]),"+f"(d[7])
    : "r"(a0), "r"(a1), "r"(a2), "r"(a3), "l"(db), "r"(sd));
}
__device__ __forceinline__ void rsb(float (&d)[16], uint32_t a0, uint32_t a1, uint32_t a2, uint32_t a3, uint64_t db, int sd) {
  asm volatile("{\n.reg .pred p;\nsetp.ne.b32 p, %21, 0;\n"
    "wgmma.mma_async.sync.aligned.m64n32k16.f32.bf16.bf16 "
    "{%0,%1,%2,%3,%4,%5,%6,%7,%8,%9,%10,%11,%12,%13,%14,%15},{%16,%17,%18,%19},%20,p,1,1,1;\n}\n"
    : "+f"(d[0]),"+f"(d[1]),"+f"(d[2]),"+f"(d[3]),"+f"(d[4]),"+f"(d[5]),"+f"(d[6]),"+f"(d[7]),"+f"(d[8]),"+f"(d[9]),"+f"(d[10]),"+f"(d[11]),"+f"(d[12]),"+f"(d[13]),"+f"(d[14]),"+f"(d[15])
    : "r"(a0), "r"(a1), "r"(a2), "r"(a3), "l"(db), "r"(sd));
}
__device__ __forceinline__ void rsb(float (&d)[24], uint32_t a0, uint32_t a1, uint32_t a2, uint32_t a3, uint64_t db, int sd) {
  asm volatile("{\n.reg .pred p;\nsetp.ne.b32 p, %29, 0;\n"
    "wgmma.mma_async.sync.aligned.m64n48k16.f32.bf16.bf16 "
    "{%0,%1,%2,%3,%4,%5,%6,%7,%8,%9,%10,%11,%12,%13,%14,%15,%16,%17,%18,%19,%20,%21,%22,%23},{%24,%25,%26,%27},%28,p,1,1,1;\n}\n"
    : "+f"(d[0]),"+f"(d[1]),"+f"(d[2]),"+f"(d[3]),"+f"(d[4]),"+f"(d[5]),"+f"(d[6]),"+f"(d[7]),"+f"(d[8]),"+f"(d[9]),"+f"(d[10]),"+f"(d[11]),"+f"(d[12]),"+f"(d[13]),"+f"(d[14]),"+f"(d[15]),"+f"(d[16]),"+f"(d[17]),"+f"(d[18]),"+f"(d[19]),"+f"(d[20]),"+f"(d[21]),"+f"(d[22]),"+f"(d[23])
    : "r"(a0), "r"(a1), "r"(a2), "r"(a3), "l"(db), "r"(sd));
}
__device__ __forceinline__ void rsb(float (&d)[48], uint32_t a0, uint32_t a1, uint32_t a2, uint32_t a3, uint64_t db, int sd) {
  asm volatile("{\n.reg .pred p;\nsetp.ne.b32 p, %53, 0;\n"
    "wgmma.mma_async.sync.aligned.m64n96k16.f32.bf16.bf16 "
    "{%0,%1,%2,%3,%4,%5,%6,%7,%8,%9,%10,%11,%12,%13,%14,%15,%16,%17,%18,%19,%20,%21,%22,%23,%24,%25,%26,%27,%28,%29,%30,%31,%32,%33,%34,%35,%36,%37,%38,%39,%40,%41,%42,%43,%44,%45,%46,%47},{%48,%49,%50,%51},%52,p,1,1,1;\n}\n"
    : "+f"(d[0]),"+f"(d[1]),"+f"(d[2]),"+f"(d[3]),"+f"(d[4]),"+f"(d[5]),"+f"(d[6]),"+f"(d[7]),"+f"(d[8]),"+f"(d[9]),"+f"(d[10]),"+f"(d[11]),"+f"(d[12]),"+f"(d[13]),"+f"(d[14]),"+f"(d[15]),"+f"(d[16]),"+f"(d[17]),"+f"(d[18]),"+f"(d[19]),"+f"(d[20]),"+f"(d[21]),"+f"(d[22]),"+f"(d[23]),"+f"(d[24]),"+f"(d[25]),"+f"(d[26]),"+f"(d[27]),"+f"(d[28]),"+f"(d[29]),"+f"(d[30]),"+f"(d[31]),"+f"(d[32]),"+f"(d[33]),"+f"(d[34]),"+f"(d[35]),"+f"(d[36]),"+f"(d[37]),"+f"(d[38]),"+f"(d[39]),"+f"(d[40]),"+f"(d[41]),"+f"(d[42]),"+f"(d[43]),"+f"(d[44]),"+f"(d[45]),"+f"(d[46]),"+f"(d[47])
    : "r"(a0), "r"(a1), "r"(a2), "r"(a3), "l"(db), "r"(sd));
}
__device__ __forceinline__ void rsb(float (&d)[56], uint32_t a0, uint32_t a1, uint32_t a2, uint32_t a3, uint64_t db, int sd) {
  asm volatile("{\n.reg .pred p;\nsetp.ne.b32 p, %61, 0;\n"
    "wgmma.mma_async.sync.aligned.m64n112k16.f32.bf16.bf16 "
    "{%0,%1,%2,%3,%4,%5,%6,%7,%8,%9,%10,%11,%12,%13,%14,%15,%16,%17,%18,%19,%20,%21,%22,%23,%24,%25,%26,%27,%28,%29,%30,%31,%32,%33,%34,%35,%36,%37,%38,%39,%40,%41,%42,%43,%44,%45,%46,%47,%48,%49,%50,%51,%52,%53,%54,%55},{%56,%57,%58,%59},%60,p,1,1,1;\n}\n"
    : "+f"(d[0]),"+f"(d[1]),"+f"(d[2]),"+f"(d[3]),"+f"(d[4]),"+f"(d[5]),"+f"(d[6]),"+f"(d[7]),"+f"(d[8]),"+f"(d[9]),"+f"(d[10]),"+f"(d[11]),"+f"(d[12]),"+f"(d[13]),"+f"(d[14]),"+f"(d[15]),"+f"(d[16]),"+f"(d[17]),"+f"(d[18]),"+f"(d[19]),"+f"(d[20]),"+f"(d[21]),"+f"(d[22]),"+f"(d[23]),"+f"(d[24]),"+f"(d[25]),"+f"(d[26]),"+f"(d[27]),"+f"(d[28]),"+f"(d[29]),"+f"(d[30]),"+f"(d[31]),"+f"(d[32]),"+f"(d[33]),"+f"(d[34]),"+f"(d[35]),"+f"(d[36]),"+f"(d[37]),"+f"(d[38]),"+f"(d[39]),"+f"(d[40]),"+f"(d[41]),"+f"(d[42]),"+f"(d[43]),"+f"(d[44]),"+f"(d[45]),"+f"(d[46]),"+f"(d[47]),"+f"(d[48]),"+f"(d[49]),"+f"(d[50]),"+f"(d[51]),"+f"(d[52]),"+f"(d[53]),"+f"(d[54]),"+f"(d[55])
    : "r"(a0), "r"(a1), "r"(a2), "r"(a3), "l"(db), "r"(sd));
}
__device__ __forceinline__ void rsb(float (&d)[64], uint32_t a0, uint32_t a1, uint32_t a2, uint32_t a3, uint64_t db, int sd) {
  asm volatile("{\n.reg .pred p;\nsetp.ne.b32 p, %69, 0;\n"
    "wgmma.mma_async.sync.aligned.m64n128k16.f32.bf16.bf16 "
    "{%0,%1,%2,%3,%4,%5,%6,%7,%8,%9,%10,%11,%12,%13,%14,%15,%16,%17,%18,%19,%20,%21,%22,%23,%24,%25,%26,%27,%28,%29,%30,%31,%32,%33,%34,%35,%36,%37,%38,%39,%40,%41,%42,%43,%44,%45,%46,%47,%48,%49,%50,%51,%52,%53,%54,%55,%56,%57,%58,%59,%60,%61,%62,%63},{%64,%65,%66,%67},%68,p,1,1,1;\n}\n"
    : "+f"(d[0]),"+f"(d[1]),"+f"(d[2]),"+f"(d[3]),"+f"(d[4]),"+f"(d[5]),"+f"(d[6]),"+f"(d[7]),"+f"(d[8]),"+f"(d[9]),"+f"(d[10]),"+f"(d[11]),"+f"(d[12]),"+f"(d[13]),"+f"(d[14]),"+f"(d[15]),"+f"(d[16]),"+f"(d[17]),"+f"(d[18]),"+f"(d[19]),"+f"(d[20]),"+f"(d[21]),"+f"(d[22]),"+f"(d[23]),"+f"(d[24]),"+f"(d[25]),"+f"(d[26]),"+f"(d[27]),"+f"(d[28]),"+f"(d[29]),"+f"(d[30]),"+f"(d[31]),"+f"(d[32]),"+f"(d[33]),"+f"(d[34]),"+f"(d[35]),"+f"(d[36]),"+f"(d[37]),"+f"(d[38]),"+f"(d[39]),"+f"(d[40]),"+f"(d[41]),"+f"(d[42]),"+f"(d[43]),"+f"(d[44]),"+f"(d[45]),"+f"(d[46]),"+f"(d[47]),"+f"(d[48]),"+f"(d[49]),"+f"(d[50]),"+f"(d[51]),"+f"(d[52]),"+f"(d[53]),"+f"(d[54]),"+f"(d[55]),"+f"(d[56]),"+f"(d[57]),"+f"(d[58]),"+f"(d[59]),"+f"(d[60]),"+f"(d[61]),"+f"(d[62]),"+f"(d[63])
    : "r"(a0), "r"(a1), "r"(a2), "r"(a3), "l"(db), "r"(sd));
}
__device__ __forceinline__ void rsb(float (&d)[72], uint32_t a0, uint32_t a1, uint32_t a2, uint32_t a3, uint64_t db, int sd) {
  asm volatile("{\n.reg .pred p;\nsetp.ne.b32 p, %77, 0;\n"
    "wgmma.mma_async.sync.aligned.m64n144k16.f32.bf16.bf16 "
    "{%0,%1,%2,%3,%4,%5,%6,%7,%8,%9,%10,%11,%12,%13,%14,%15,%16,%17,%18,%19,%20,%21,%22,%23,%24,%25,%26,%27,%28,%29,%30,%31,%32,%33,%34,%35,%36,%37,%38,%39,%40,%41,%42,%43,%44,%45,%46,%47,%48,%49,%50,%51,%52,%53,%54,%55,%56,%57,%58,%59,%60,%61,%62,%63,%64,%65,%66,%67,%68,%69,%70,%71},{%72,%73,%74,%75},%76,p,1,1,1;\n}\n"
    : "+f"(d[0]),"+f"(d[1]),"+f"(d[2]),"+f"(d[3]),"+f"(d[4]),"+f"(d[5]),"+f"(d[6]),"+f"(d[7]),"+f"(d[8]),"+f"(d[9]),"+f"(d[10]),"+f"(d[11]),"+f"(d[12]),"+f"(d[13]),"+f"(d[14]),"+f"(d[15]),"+f"(d[16]),"+f"(d[17]),"+f"(d[18]),"+f"(d[19]),"+f"(d[20]),"+f"(d[21]),"+f"(d[22]),"+f"(d[23]),"+f"(d[24]),"+f"(d[25]),"+f"(d[26]),"+f"(d[27]),"+f"(d[28]),"+f"(d[29]),"+f"(d[30]),"+f"(d[31]),"+f"(d[32]),"+f"(d[33]),"+f"(d[34]),"+f"(d[35]),"+f"(d[36]),"+f"(d[37]),"+f"(d[38]),"+f"(d[39]),"+f"(d[40]),"+f"(d[41]),"+f"(d[42]),"+f"(d[43]),"+f"(d[44]),"+f"(d[45]),"+f"(d[46]),"+f"(d[47]),"+f"(d[48]),"+f"(d[49]),"+f"(d[50]),"+f"(d[51]),"+f"(d[52]),"+f"(d[53]),"+f"(d[54]),"+f"(d[55]),"+f"(d[56]),"+f"(d[57]),"+f"(d[58]),"+f"(d[59]),"+f"(d[60]),"+f"(d[61]),"+f"(d[62]),"+f"(d[63]),"+f"(d[64]),"+f"(d[65]),"+f"(d[66]),"+f"(d[67]),"+f"(d[68]),"+f"(d[69]),"+f"(d[70]),"+f"(d[71])
    : "r"(a0), "r"(a1), "r"(a2), "r"(a3), "l"(db), "r"(sd));
}
__device__ __forceinline__ void mm160(float (&d)[80], uint64_t da, uint64_t db, int sd) {
  asm volatile("{\n.reg .pred p;\nsetp.ne.b32 p, %82, 0;\n"
    "wgmma.mma_async.sync.aligned.m64n160k16.f32.bf16.bf16 "
    "{%0,%1,%2,%3,%4,%5,%6,%7,%8,%9,%10,%11,%12,%13,%14,%15,%16,%17,%18,%19,%20,%21,%22,%23,%24,%25,%26,%27,%28,%29,%30,%31,%32,%33,%34,%35,%36,%37,%38,%39,%40,%41,%42,%43,%44,%45,%46,%47,%48,%49,%50,%51,%52,%53,%54,%55,%56,%57,%58,%59,%60,%61,%62,%63,%64,%65,%66,%67,%68,%69,%70,%71,%72,%73,%74,%75,%76,%77,%78,%79},%80,%81,p,1,1,0,0;\n}\n"
    : "+f"(d[0]),"+f"(d[1]),"+f"(d[2]),"+f"(d[3]),"+f"(d[4]),"+f"(d[5]),"+f"(d[6]),"+f"(d[7]),"+f"(d[8]),"+f"(d[9]),"+f"(d[10]),"+f"(d[11]),"+f"(d[12]),"+f"(d[13]),"+f"(d[14]),"+f"(d[15]),"+f"(d[16]),"+f"(d[17]),"+f"(d[18]),"+f"(d[19]),"+f"(d[20]),"+f"(d[21]),"+f"(d[22]),"+f"(d[23]),"+f"(d[24]),"+f"(d[25]),"+f"(d[26]),"+f"(d[27]),"+f"(d[28]),"+f"(d[29]),"+f"(d[30]),"+f"(d[31]),"+f"(d[32]),"+f"(d[33]),"+f"(d[34]),"+f"(d[35]),"+f"(d[36]),"+f"(d[37]),"+f"(d[38]),"+f"(d[39]),"+f"(d[40]),"+f"(d[41]),"+f"(d[42]),"+f"(d[43]),"+f"(d[44]),"+f"(d[45]),"+f"(d[46]),"+f"(d[47]),"+f"(d[48]),"+f"(d[49]),"+f"(d[50]),"+f"(d[51]),"+f"(d[52]),"+f"(d[53]),"+f"(d[54]),"+f"(d[55]),"+f"(d[56]),"+f"(d[57]),"+f"(d[58]),"+f"(d[59]),"+f"(d[60]),"+f"(d[61]),"+f"(d[62]),"+f"(d[63]),"+f"(d[64]),"+f"(d[65]),"+f"(d[66]),"+f"(d[67]),"+f"(d[68]),"+f"(d[69]),"+f"(d[70]),"+f"(d[71]),"+f"(d[72]),"+f"(d[73]),"+f"(d[74]),"+f"(d[75]),"+f"(d[76]),"+f"(d[77]),"+f"(d[78]),"+f"(d[79])
    : "l"(da), "l"(db), "r"(sd));
}
__device__ __forceinline__ void mmt(float (&d)[64], uint64_t da, uint64_t db, int sd) {
  asm volatile("{\n.reg .pred p;\nsetp.ne.b32 p, %66, 0;\n"
    "wgmma.mma_async.sync.aligned.m64n128k16.f32.bf16.bf16 "
    "{%0,%1,%2,%3,%4,%5,%6,%7,%8,%9,%10,%11,%12,%13,%14,%15,%16,%17,%18,%19,%20,%21,%22,%23,%24,%25,%26,%27,%28,%29,%30,%31,%32,%33,%34,%35,%36,%37,%38,%39,%40,%41,%42,%43,%44,%45,%46,%47,%48,%49,%50,%51,%52,%53,%54,%55,%56,%57,%58,%59,%60,%61,%62,%63},%64,%65,p,1,1,1,0;\n}\n"
    : "+f"(d[0]),"+f"(d[1]),"+f"(d[2]),"+f"(d[3]),"+f"(d[4]),"+f"(d[5]),"+f"(d[6]),"+f"(d[7]),"+f"(d[8]),"+f"(d[9]),"+f"(d[10]),"+f"(d[11]),"+f"(d[12]),"+f"(d[13]),"+f"(d[14]),"+f"(d[15]),"+f"(d[16]),"+f"(d[17]),"+f"(d[18]),"+f"(d[19]),"+f"(d[20]),"+f"(d[21]),"+f"(d[22]),"+f"(d[23]),"+f"(d[24]),"+f"(d[25]),"+f"(d[26]),"+f"(d[27]),"+f"(d[28]),"+f"(d[29]),"+f"(d[30]),"+f"(d[31]),"+f"(d[32]),"+f"(d[33]),"+f"(d[34]),"+f"(d[35]),"+f"(d[36]),"+f"(d[37]),"+f"(d[38]),"+f"(d[39]),"+f"(d[40]),"+f"(d[41]),"+f"(d[42]),"+f"(d[43]),"+f"(d[44]),"+f"(d[45]),"+f"(d[46]),"+f"(d[47]),"+f"(d[48]),"+f"(d[49]),"+f"(d[50]),"+f"(d[51]),"+f"(d[52]),"+f"(d[53]),"+f"(d[54]),"+f"(d[55]),"+f"(d[56]),"+f"(d[57]),"+f"(d[58]),"+f"(d[59]),"+f"(d[60]),"+f"(d[61]),"+f"(d[62]),"+f"(d[63])
    : "l"(da), "l"(db), "r"(sd));
}
__device__ __forceinline__ void mmt(float (&d)[32], uint64_t da, uint64_t db, int sd) {
  asm volatile("{\n.reg .pred p;\nsetp.ne.b32 p, %34, 0;\n"
    "wgmma.mma_async.sync.aligned.m64n64k16.f32.bf16.bf16 "
    "{%0,%1,%2,%3,%4,%5,%6,%7,%8,%9,%10,%11,%12,%13,%14,%15,%16,%17,%18,%19,%20,%21,%22,%23,%24,%25,%26,%27,%28,%29,%30,%31},%32,%33,p,1,1,1,0;\n}\n"
    : "+f"(d[0]),"+f"(d[1]),"+f"(d[2]),"+f"(d[3]),"+f"(d[4]),"+f"(d[5]),"+f"(d[6]),"+f"(d[7]),"+f"(d[8]),"+f"(d[9]),"+f"(d[10]),"+f"(d[11]),"+f"(d[12]),"+f"(d[13]),"+f"(d[14]),"+f"(d[15]),"+f"(d[16]),"+f"(d[17]),"+f"(d[18]),"+f"(d[19]),"+f"(d[20]),"+f"(d[21]),"+f"(d[22]),"+f"(d[23]),"+f"(d[24]),"+f"(d[25]),"+f"(d[26]),"+f"(d[27]),"+f"(d[28]),"+f"(d[29]),"+f"(d[30]),"+f"(d[31])
    : "l"(da), "l"(db), "r"(sd));
}
__device__ __forceinline__ void qk64h(uint32_t (&d)[16], uint32_t a0, uint32_t a1, uint32_t a2, uint32_t a3, uint64_t db, int sd) {
  asm volatile("{\n.reg .pred p;\nsetp.ne.b32 p, %21, 0;\n"
    "wgmma.mma_async.sync.aligned.m64n64k16.f16.f16.f16 "
    "{%0,%1,%2,%3,%4,%5,%6,%7,%8,%9,%10,%11,%12,%13,%14,%15},{%16,%17,%18,%19},%20,p,1,1,0;\n}\n"
    : "+r"(d[0]),"+r"(d[1]),"+r"(d[2]),"+r"(d[3]),"+r"(d[4]),"+r"(d[5]),"+r"(d[6]),"+r"(d[7]),"+r"(d[8]),"+r"(d[9]),"+r"(d[10]),"+r"(d[11]),"+r"(d[12]),"+r"(d[13]),"+r"(d[14]),"+r"(d[15])
    : "r"(a0), "r"(a1), "r"(a2), "r"(a3), "l"(db), "r"(sd));
}
__device__ __forceinline__ void pv24h(uint32_t (&d)[6], uint32_t a0, uint32_t a1, uint32_t a2, uint32_t a3, uint64_t db, int sd) {
  asm volatile("{\n.reg .pred p;\nsetp.ne.b32 p, %11, 0;\n"
    "wgmma.mma_async.sync.aligned.m64n24k16.f16.f16.f16 "
    "{%0,%1,%2,%3,%4,%5},{%6,%7,%8,%9},%10,p,1,1,1;\n}\n"
    : "+r"(d[0]),"+r"(d[1]),"+r"(d[2]),"+r"(d[3]),"+r"(d[4]),"+r"(d[5])
    : "r"(a0), "r"(a1), "r"(a2), "r"(a3), "l"(db), "r"(sd));
}
__device__ __forceinline__ void qk64f(float (&d)[32], uint32_t a0, uint32_t a1, uint32_t a2, uint32_t a3, uint64_t db, int sd) {
  asm volatile("{\n.reg .pred p;\nsetp.ne.b32 p, %37, 0;\n"
    "wgmma.mma_async.sync.aligned.m64n64k16.f32.f16.f16 "
    "{%0,%1,%2,%3,%4,%5,%6,%7,%8,%9,%10,%11,%12,%13,%14,%15,%16,%17,%18,%19,%20,%21,%22,%23,%24,%25,%26,%27,%28,%29,%30,%31},{%32,%33,%34,%35},%36,p,1,1,0;\n}\n"
    : "+f"(d[0]),"+f"(d[1]),"+f"(d[2]),"+f"(d[3]),"+f"(d[4]),"+f"(d[5]),"+f"(d[6]),"+f"(d[7]),"+f"(d[8]),"+f"(d[9]),"+f"(d[10]),"+f"(d[11]),"+f"(d[12]),"+f"(d[13]),"+f"(d[14]),"+f"(d[15]),"+f"(d[16]),"+f"(d[17]),"+f"(d[18]),"+f"(d[19]),"+f"(d[20]),"+f"(d[21]),"+f"(d[22]),"+f"(d[23]),"+f"(d[24]),"+f"(d[25]),"+f"(d[26]),"+f"(d[27]),"+f"(d[28]),"+f"(d[29]),"+f"(d[30]),"+f"(d[31])
    : "r"(a0), "r"(a1), "r"(a2), "r"(a3), "l"(db), "r"(sd));
}
__device__ __forceinline__ void pv24f(float (&d)[12], uint32_t a0, uint32_t a1, uint32_t a2, uint32_t a3, uint64_t db, int sd) {
  asm volatile("{\n.reg .pred p;\nsetp.ne.b32 p, %17, 0;\n"
    "wgmma.mma_async.sync.aligned.m64n24k16.f32.f16.f16 "
    "{%0,%1,%2,%3,%4,%5,%6,%7,%8,%9,%10,%11},{%12,%13,%14,%15},%16,p,1,1,1;\n}\n"
    : "+f"(d[0]),"+f"(d[1]),"+f"(d[2]),"+f"(d[3]),"+f"(d[4]),"+f"(d[5]),"+f"(d[6]),"+f"(d[7]),"+f"(d[8]),"+f"(d[9]),"+f"(d[10]),"+f"(d[11])
    : "r"(a0), "r"(a1), "r"(a2), "r"(a3), "l"(db), "r"(sd));
}

constexpr uint32_t SW128 = 0x40000000u;
constexpr int NCTA = 132, NSSM = 117;
constexpr int PAD = 6;
constexpr int D0 = 1000, DP = 180;
constexpr int NEXP = 11;
constexpr int THR = 40;

constexpr uint32_t A_ST = 49152;
constexpr uint32_t B_ST = 36864;
constexpr uint32_t KV_OFF = 62464;
constexpr uint32_t C_ST = 26624, Y_OFF = 18944;
constexpr uint32_t X_OFF = 51200;
constexpr uint32_t W_OFF = 144384;
constexpr uint32_t T_STG = 212992;
constexpr uint32_t CONSTS = 226304, EXCH = CONSTS;
constexpr uint32_t P_OFF = 231424;
constexpr uint32_t FULL_A = P_OFF, EMPTY_A = P_OFF + 32, FULL_B = P_OFF + 64, EMPTY_B = P_OFF + 480, FULL_HI = P_OFF + 112, FULL_LO = P_OFF + 120,
                   Q_READY = P_OFF + 128, STG_FREE = P_OFF + 136, FULL_X = P_OFF + 144, FULL_C = P_OFF + 360,
                   KV_FREE = P_OFF + 192, FULL_W = P_OFF + 200, FULL_O = P_OFF + 208, HAVE_ST = P_OFF + 216,
                   PART = P_OFF + 312, EPOCH = P_OFF + 296, XLOCK = P_OFF + 332, STATS = P_OFF + 288, ZERO = P_OFF + 300, PUB = P_OFF + 152, LAND_HI = P_OFF + 96, LAND_LO = P_OFF + 160, STAGED = P_OFF + 168, PF_GO = P_OFF + 176, SINK = P_OFF + 464;
constexpr int SMEM = 232448;

__device__ __forceinline__ void cp16(uint32_t dst, const void* src) { asm volatile("cp.async.cg.shared.global [%0], [%1], 16;" ::"r"(dst), "l"(src) : "memory"); }
__device__ __forceinline__ bool elect() {
  uint32_t r;
  asm volatile("{\n.reg .pred p;\nelect.sync _|p, 0xffffffff;\nselp.u32 %0, 1, 0, p;\n}\n" : "=r"(r));
  return r;
}
__device__ __forceinline__ uint32_t* cnt(int i) { return g_cnt + i * 64; }
__device__ __forceinline__ uint32_t stg_off(int u) { return u ? 131072 + u * 16384 : 196608; }
__device__ __forceinline__ uint32_t tag(uint32_t x, uint32_t ep) { uint32_t r; asm("lop3.b32 %0, %1, %2, 1, 0xD8;" : "=r"(r) : "r"(x), "r"(ep)); return r; }
template <class T> __device__ __forceinline__ void pinl(T& x) { asm volatile("" : "+l"(x)); }
template <int L> __device__ __forceinline__ uint32_t lop3(uint32_t a, uint32_t b, uint32_t c) { uint32_t r; asm("lop3.b32 %0, %1, %2, %3, %4;" : "=r"(r) : "r"(a), "r"(b), "r"(c), "n"(L)); return r; }
template <int N> __device__ __forceinline__ uint32_t stale(const uint32_t* x, uint32_t ep) {
  if constexpr (N == 1) return x[0] ^ ep;
  else if constexpr (N == 2) return lop3<0x7E>(x[0], x[1], ep);
  else { constexpr int A = (N / 3 + 1) & ~1, B = N - 2 * A > 0 ? A : N - A;
    if constexpr (N - A - B > 0) return lop3<0xFE>(stale<A>(x, ep), stale<B>(x + A, ep), stale<N - A - B>(x + A + B, ep));
    else return lop3<0xFC>(stale<A>(x, ep), stale<B>(x + A, ep), 0); }
}
__device__ __forceinline__ float rcp_a(float x) { float y; asm("rcp.approx.ftz.f32 %0, %1;" : "=f"(y) : "f"(x)); return y; }
struct Ptrs { const __nv_bfloat16 *xa, *lre, *lim, *br, *bi, *cr, *ci, *ldt, *dsk, *xb, *w, *wo; float* out; };
struct Maps { CUtensorMap xb, w, q, kv, bb, xa20, xa16, hs20, hs16, hl, cr, ci, xs, out, out2, cr2, ci2; };

struct cf { float r, i; };
__device__ __forceinline__ cf cmul(cf a, cf b) { return {a.r * b.r - a.i * b.i, a.r * b.i + a.i * b.r}; }
__device__ __forceinline__ cf cfma(cf a, cf b, cf c) { return {fmaf(a.r, b.r, fmaf(-a.i, b.i, c.r)), fmaf(a.r, b.i, fmaf(a.i, b.r, c.i))}; }
__device__ __forceinline__ cf cshfl_up(cf a, int d) { return {__shfl_up_sync(0xffffffffu, a.r, d, 4), __shfl_up_sync(0xffffffffu, a.i, d, 4)}; }

__device__ __forceinline__ uint32_t e_fma(uint32_t a, uint32_t b, uint32_t c) { uint32_t r; asm("fma.rn.f16x2 %0, %1, %2, %3;" : "=r"(r) : "r"(a), "r"(b), "r"(c)); return r; }
__device__ __forceinline__ uint32_t e_int(uint32_t x2) { uint32_t r; asm("fma.rn.relu.f16x2 %0, %1, %2, %3;" : "=r"(r) : "r"(x2), "r"(0x02000200u), "r"(0u)); return r; }
__device__ __forceinline__ uint32_t e_ins(uint32_t r, uint32_t p) { uint32_t s; asm("{\n.reg .b32 t;\nshf.l.wrap.b32 t, %1, %2, 10;\nadd.u32 %0, t, %3;\n}" : "=r"(s) : "r"(0), "r"(r), "r"(p)); return s; }
__device__ __forceinline__ uint32_t exp2_fma(uint32_t x2, uint32_t c2) {
  const uint32_t r = e_int(x2), f = e_fma(r, 0xF800F800u, x2);
  return e_ins(r, e_fma(e_fma(f, c2, 0x29A029A0u), f, 0x08000800u));
}
__device__ __forceinline__ uint32_t exp2_mufu(uint32_t x) { uint32_t y; asm("ex2.approx.f16x2 %0, %1;" : "=r"(y) : "r"(x)); return y; }
__device__ __forceinline__ void exp_chunk(uint32_t (&p)[16], const uint32_t (&s)[16], uint32_t c2) {
#pragma unroll
  for (int j = 0; j < 16; j++) p[j] = j >= 10 ? exp2_mufu(s[j]) : exp2_fma(s[j], c2);
}
__device__ __forceinline__ void qk_h(uint32_t (&s)[16], const uint32_t (&q)[8], uint32_t k, uint32_t kt, int o) {
  qk64h(s, q[0], q[1], q[2], q[3], mkdesc(k, 8) + o, 0);
  qk64h(s, q[4], q[5], q[6], q[7], mkdesc(kt, 8) + o, 1);
}
__device__ __forceinline__ void pv_h(uint32_t (&a)[6], const uint32_t (&p)[16], uint32_t v, int o) {
#pragma unroll
  for (int kk = 0; kk < 4; kk++) pv24h(a, p[4 * kk], p[4 * kk + 1], p[4 * kk + 2], p[4 * kk + 3], mkdesc(v, 128) + (o + 16 * kk), 1);
}

__device__ __forceinline__ uint32_t k_const(int key) { return (key & 63) >= 40 ? 0xDA804C00u : 0x00002800u; }
__device__ __forceinline__ const uint32_t* tails_ptr(int c, int t) {
  return g_t + ((4 + (blockIdx.x >> 5)) * 32 + 2 * c + (t >> 6)) * 512 + (blockIdx.x >> 2 & 7) * 64 + (t & 63);
}
template <int S, int N> __device__ __forceinline__ void tails_ld(uint32_t (&k)[N], uint32_t (&v)[N], int c0, const uint32_t* p = nullptr) {
  if (!p) p = tails_ptr(c0, tid_v() & 127);
#pragma unroll
  for (int i = 0; i < N; i++) { k[i] = ld_l2(p + i * S * 1024); v[i] = ld_l2(p + 65536 + i * S * 1024); }
}
template <int S, int N> __device__ __forceinline__ void tails_st(uint32_t (&k)[N], uint32_t (&v)[N], int c0, uint32_t sb) {
  const int t = tid_v() & 127;
  const uint32_t ep = lds32(sb + EPOCH);
  for (uint32_t n = 0;;) {
    if (!__any_sync(0xffffffffu, lop3<0xA8>(stale<N>(k, ep), stale<N>(v, ep), 1))) break;
    tails_ld<S>(k, v, c0);
    if (++n > (1u << 21)) __trap();
  }
#pragma unroll
  for (int i = 0; i < N; i++)
    if (S == 1 || i < N - 1 || c0 == 0) sts128(sb + KV_OFF + (c0 + S * i) * 10240 + 8192 + t * 16, k[i], k_const(t), v[i], 0x00003C00u);
  fence_async();
}
__device__ __forceinline__ void fetch_kv(uint32_t sb, int c, int n, uint32_t land, int total) {
  if (elect()) {
    if (total) mbar_expect(sb + land, total * 8192);
#pragma unroll 1
    for (int i = c; i > c - n; i--) bulk_g2s(sb + KV_OFF + i * 10240, g_kv + (blockIdx.x >> 2) * 131072 + i * 8192, 8192, sb + land);
  }
}
template <int C, int N, int T> __device__ __forceinline__ void check_kv(uint32_t sb, uint32_t land, uint32_t full) {
  constexpr int P = 256 / T;
  const uint32_t t = tid_v() & (T - 1), ep = lds32(sb + EPOCH), a = sb + KV_OFF + C * 10240 + t * 32, o = t & 28;
  uint32_t x[N * P];
  mbar_wait(sb + land, 0);
#pragma unroll
  for (int i = 0; i < N * P; i++) x[i] = lds32(a + o - i / P * 10240 + i % P * 4096);
  if (__any_sync(0xffffffffu, lop3<0xC0>(stale<N * P>(x, ep), 1, 0))) {
#pragma unroll 1
    for (int i = 0; i < N * P; i++) {
      const uint32_t s = a - i / P * 10240 + i % P * 4096;
      const uint8_t* g = g_kv + (blockIdx.x >> 2) * 131072 + (C - i / P) * 8192 + i % P * 4096 + t * 32;
      asm volatile("{\n.reg .pred p, q;\n.reg .u32 n, m, a, b, c, d, e, f, g, h;\nmov.u32 n, 0;\n"
                   "ld.shared.b32 m, [%3];\nlop3.b32 m, m, %2, 1, 0x28;\nsetp.ne.u32 p, m, 0;\n"
                   "W:\nvote.sync.any.pred q, p, 0xffffffff;\n@!q bra.uni E;\n"
                   "ld.relaxed.gpu.global.v4.u32 {a, b, c, d}, [%1];\nld.relaxed.gpu.global.v4.u32 {e, f, g, h}, [%1 + 16];\n"
                   "lop3.b32 m, a, e, %2, 0x7E;\nand.b32 m, m, 1;\nsetp.ne.u32 p, m, 0;\n"
                   "st.shared.v4.b32 [%0], {a, b, c, d};\nst.shared.v4.b32 [%0 + 16], {e, f, g, h};\n"
                   "add.u32 n, n, 1;\nsetp.lt.u32 q, n, 2097152;\n@q bra.uni W;\ntrap;\nE:\n}\n" ::"r"(s), "l"(g), "r"(ep), "r"(s + o) : "memory");
    }
    fence_async();
  }
  __syncwarp();
  if ((t & 31) == 0) mbar_arrive(sb + full);
}

template <int HG> __device__ __forceinline__ void qkv_loop(uint32_t (&pk)[36], uint32_t sb, uint32_t arow, bool first) {
  constexpr int N0 = HG ? 32 - 8 * HG : 8;
  float a[N0], c[HG ? 72 - N0 : 72];
#pragma unroll 1
  for (int kb = 0; kb < 9; kb++) {
    const uint32_t st = ((kb + 3) & 3) * A_ST, lb = ((sb + st + 24576) >> 4) | (512u << 16);
    uint32_t f[4][4], aa[4];
#pragma unroll
    for (int kk = 0; kk < 4; kk++) { aa[kk] = (arow + st) ^ (kk << 5); pin(aa[kk]); }
    mbar_wait(sb + FULL_A + 8 * (kb & 3), (kb >> 2) & 1);
#pragma unroll
    for (int kk = 0; kk < 4; kk++) ldsm4(f[kk], aa[kk]);
    wfence();
#pragma unroll
    for (int kk = 0; kk < 4; kk++) {
      if (HG) rsb(a, f[kk][0], f[kk][1], f[kk][2], f[kk][3], mkdesc(lb + kk * 128 + 2 * HG, SW128 | 64), kk ? 1 : kb);
      rsb(c, f[kk][0], f[kk][1], f[kk][2], f[kk][3], mkdesc(lb + kk * 128 + (HG ? 512 : 0), SW128 | 64), kk ? 1 : kb);
    }
    wcommit();
    wwait<0>();
    if (first) mbar_arrive(sb + EMPTY_A + 8 * (kb & 3));
  }
  if (HG) fence_regs(a);
  fence_regs(c);
#pragma unroll
  for (int j = 0; j < 36; j++) {
    const float* x = HG && 2 * j < N0 ? a + 2 * j : c + 2 * j - (HG ? N0 : 0);
    pk[j] = packh(x[0], x[1]);
  }
}
__global__ void __launch_bounds__(512, 1)
k_fused(const __grid_constant__ Maps mp, const __grid_constant__ Ptrs pp) {
  extern __shared__ __align__(1024) uint8_t smem_raw[];
  const uint32_t sb = smem_u32(smem_raw);
  if (threadIdx.x == 384) {
    tmap_prefetch(&mp.xb); tmap_prefetch(&mp.w);
    for (int i = 0; i < 4; i++) mbar_init(sb + FULL_A + 8 * i, 1);
    mbar_init_fence(); fence_async();
    const uint32_t b = blockIdx.x, type = b / 44;
    mbar_expect(sb + FULL_A, A_ST);
    tma3d(sb + 3 * A_ST + 24576, &mp.w, 0, 0, ((type * 4 + (b & 3)) * 9) >> 2, sb + FULL_A);
    tma3d(sb + 3 * A_ST, &mp.xb, 0, ((b - type * 44) >> 2) * 192, 0, sb + FULL_A);
  }
  __syncwarp();
  const int wg = __shfl_sync(0xffffffffu, threadIdx.x >> 7, 0);
  uint32_t q[8];
  auto load_q = [&](int u, uint32_t bar = 0) {
    const int b = bid_v(), t = tid_v() & 127, head = b >> 2, unit = 31 - 4 * u - (b & 3), row = (t >> 5) * 16 + ((t & 31) >> 2), qd = t & 3;
    const uint8_t* qp = g_q + head * 65536 + (unit >> 1) * 4096 + ((unit & 1) * 64 + row) * 16 + qd * 4;
    const uint32_t* tp = g_t + ((head >> 3) * 32 + unit) * 512 + (head & 7) * 64 + row;
    if (bar) { pinl(qp); pinl(tp); mbar_wait(sb + bar, 0); }
    q[0] = ld_l2(qp); q[1] = ld_l2(qp + 128); q[2] = ld_l2(qp + 2048); q[3] = ld_l2(qp + 2048 + 128);
    q[4] = q[5] = 0; q[6] = lds32(sb + ZERO); q[7] = lds32(sb + ZERO);
    if (qd == 0) { q[4] = ld_l2(tp); q[5] = ld_l2(tp + 8); }
  };
  {
    const int b = blockIdx.x, tid = threadIdx.x, t = tid & 127, lane = tid & 31, w = __shfl_sync(0xffffffffu, (tid >> 5) & 3, 0), g = lane >> 2, qd = lane & 3;
    const int type = b / 44, rt = (b % 44) >> 2, hg = b & 3;
    const bool ssm = b < NSSM;
    const int pt = (b / 39) * 3 + (b % 39) % 3, tt = (b % 39) / 3;
    const int J = tt == 12 ? 16 : 20;
    auto load_a = [&](int kb) {
      const uint32_t st = sb + ((kb + 3) & 3) * A_ST, fb = sb + FULL_A + 8 * (kb & 3);
      if (w == 0) mbar_expect(fb, A_ST);
      tma3d(st + w * 24576, &mp.xb + w, w ? 0 : kb * 64, w ? kb * 64 : rt * 192, w ? ((type * 4 + hg) * 9) >> 2 : 0, fb);
    };
    if (tid == 511) {
      if (sb & 1023) __trap();
      for (int i = 0; i < 4; i++) { mbar_init(sb + EMPTY_A + 8 * i, 12); mbar_init(sb + FULL_B + 8 * i, 1); mbar_init(sb + EMPTY_B + 8 * i, 8); }
      mbar_init(sb + FULL_W, 1); mbar_init(sb + FULL_O, 1); mbar_init(sb + HAVE_ST, 2);
      for (int i = 0; i < 2; i++) mbar_init(sb + FULL_C + 8 * i, 1);
      mbar_init(sb + PART, 4);
      mbar_init(sb + FULL_HI, 8); mbar_init(sb + FULL_LO, 8); mbar_init(sb + Q_READY, 1); mbar_init(sb + STG_FREE, 2); mbar_init(sb + FULL_X, 1);
      mbar_init(sb + KV_FREE, 16); mbar_init(sb + PUB, 1);
      mbar_init(sb + LAND_HI, 1); mbar_init(sb + LAND_LO, 1); mbar_init(sb + STAGED, 1); mbar_init(sb + PF_GO, 1);
      sts32(sb + XLOCK, 0); sts32(sb + ZERO, 0);
      mbar_init_fence();
    }
    __syncwarp();
    __syncthreads();
    auto load_b = [&](int kb, int s, int id) {
      const uint32_t st = sb + s * B_ST, fb = sb + FULL_B + 8 * s;
      if (id == 0) { mbar_expect(fb, J == 20 ? B_ST : 32768); tma4d(st, &mp.bb, kb * 64, 0, 0, pt * 8, fb); }
      else if (id == 1) tma5d(st + 16384, J == 20 ? &mp.xa20 : &mp.xa16, kb * 64, J == 20 ? tt : 15, fb);
    };
    auto send = [&](int i) {
      const int u = i >> 2, pu = 31 - 11 * u - rt;
      if (pu >= 0) tma3d_store(type ? &mp.kv : &mp.q, sb + stg_off(u) + (i & 3) * 4096, (pu & 1) * 256, hg * 8 + (i & 1) * 4,
                               (type == 0 ? (pu >> 1) * 2 : (pu >> 1) * 4 + (type - 1) * 2) + (i >> 1 & 1));
    };

    if (wg == 3) {
      if (w < 2) {
        for (int kb = 1; kb < 4; kb++) {
          const uint32_t c0 = clock();
          while (__all_sync(0xffffffffu, (uint32_t)clock() - c0 < (kb == 1 ? 0 : 100))) {}
          if (lane == 0) load_a(kb);
          __syncwarp();
        }
      }
      if (lane == 0) {
        if (w == 0) sts32(sb + EPOCH, atomicAdd(cnt(C_DONE), 1u) / NCTA + 1);
        if (w == 1) { tmap_prefetch(type ? &mp.kv : &mp.q); tmap_prefetch(&mp.bb); tmap_prefetch(J == 20 ? &mp.xa20 : &mp.xa16); }
        if (w == 2) { tmap_prefetch(J == 20 ? &mp.hs20 : &mp.hs16); tmap_prefetch(&mp.hl); tmap_prefetch(&mp.cr); tmap_prefetch(&mp.ci); tmap_prefetch(&mp.xs); }
        if (w == 3) { tmap_prefetch(&mp.out); tmap_prefetch(&mp.out2); }
      }
      __syncwarp();
      if (ssm && t >= 64) {
        const int p = pt * 64 + t - 64;
        const float a = __bfloat162float(pp.lre[p]), c = __bfloat162float(pp.lim[p]);
        const float dt = __bfloat162float(__float2bfloat16(expf(__bfloat162float(pp.ldt[p]))));
        const float an = __fmul_rn(dt, c), t1 = __fmul_rn(an, 0x1.45f306p-2f);
        float sn, cs;
        sincospif(fmaf(rintf(0.5f * t1), -2.f, t1) + fmaf(an, 0x1.b9391p-27f, fmaf(an, 0x1.45f306p-2f, -t1)), &sn, &cs);
        const float e = expf(dt * a);
        cf lam = {e * cs, e * sn};
        const float x = lam.r - 1.f, y = lam.i;
        cf coef;
        if (fabsf(a) >= fabsf(c)) { const float q = c / a, d = 2.f / (a + c * q); coef = {(x + y * q) * d, (y - x * q) * d}; }
        else { const float q = a / c, d = 2.f / (a * q + c); coef = {(x * q + y) * d, (y * q - x) * d}; }
        const bool swp = pp.bi < pp.br;
        if (swp) lam.i = -lam.i;
        const cf l2 = cmul(lam, lam), l4 = cmul(l2, l2), l8 = cmul(l4, l4), l16 = cmul(l8, l8), l24 = cmul(l16, l8), l32 = cmul(l16, l16);
        const cf l40 = cmul(l32, l8), l80 = cmul(l40, l40), l160 = cmul(l80, l80), l320 = cmul(l160, l160), l640 = cmul(l320, l320), l64 = cmul(l32, l32);
        const cf s1 = J == 20 ? l16 : l8, u1 = J == 20 ? l40 : l32, u2 = J == 20 ? l80 : l64;
        float4* cp = (float4*)(smem_raw + CONSTS) + (t - 64);
        cp[0] = make_float4(lam.r, lam.i, s1.r, s1.i); cp[64] = make_float4(u1.r, u1.i, u2.r, u2.i);
        cp[128] = make_float4(l24.r, l24.i, l640.r, l640.i); cp[192] = make_float4(l160.r, l160.i, l320.r, l320.i);
        cp[256] = swp ? make_float4(-coef.i, coef.r, -coef.r, -coef.i) : make_float4(coef.r, -coef.i, -coef.i, -coef.r);
      }
      __syncwarp();
      if (w < 2) {
#pragma unroll 1
        for (int kb = 4; kb < (ssm ? 13 : 9); kb++) {
          if (kb < 12) mbar_wait(sb + EMPTY_A + 8 * (kb & 3), ((kb >> 2) - 1) & 1);
          if (elect()) { if (kb < 9) load_a(kb); else load_b(kb - 9, kb - 9, w); if (kb == 8 && w == 0) mbar_arrive(sb + PF_GO); }
        }
      } else {
        mbar_wait(sb + PF_GO, 0);
#pragma unroll 1
        for (int i = t - 64; i < 340; i += 64) {
          const int m = (i - 140) / 40, l = i < 140 ? b * 140 + i : b * 40 + (i - 140) % 40;
          const __nv_bfloat16* p = i < 140 ? pp.xa : m == 0 ? pp.br : m == 1 ? pp.bi : m == 2 ? pp.cr : m == 3 ? pp.ci : pp.wo;
          if (l < (i < 140 ? 18432 : 5184)) pf_line(p + l * 64);
        }
        __syncwarp();
      }
    } else {
      const int ut = 2 - wg;
      uint32_t sa = sb + stg_off(ut) + (lane >> 4) * 8192 + (w * 16 + (lane & 15)) * 16, ta = sb + T_STG + ut * 2048 + qd * 256 + (w * 16 + g) * 4;
      uint32_t s0 = type == 0 ? 0x25712571u : type == 2 ? 0x3C003C00u : w == 3 ? 0x4C004C00u : 0x28002800u;
      uint32_t s1 = type == 0 ? 0x25712571u : type == 2 ? 0x3C003C00u : w >= 2 ? 0x4C004C00u : 0x28002800u;
      int ln = lane;
      pin(sa); pin(ta); pin(ln); pin(s0); pin(s1);
      uint32_t arow = sb + (ut * 64 + w * 16 + (lane & 15)) * 128 + (((lane >> 4) ^ (lane & 7)) << 4);
      pin(arow);
      uint32_t pk[36];
      if (hg == 0) qkv_loop<0>(pk, sb, arow, ln == 0);
      else if (hg == 1) qkv_loop<1>(pk, sb, arow, ln == 0);
      else if (hg == 2) qkv_loop<2>(pk, sb, arow, ln == 0);
      else qkv_loop<3>(pk, sb, arow, ln == 0);
      const uint32_t ep = lds32(sb + EPOCH);
      auto fin = [&](uint32_t x, int row) { return tag(hfma2(x, row ? s1 : s0, 0x80008000u), ep); };
      const int q4 = ln & 3, pos = 31 - 11 * ut - rt;
      uint32_t tl[4], ua[16];
      const bool pub = wg == 0 && w == 0;
#pragma unroll
      for (int i = 0; i < 4; i++) {
        uint32_t* x = pk + 18 * (i >> 1) + (i & 1);
        tl[i] = fin(q4 == 0 ? x[4] : q4 == 1 ? x[8] : q4 == 2 ? x[12] : x[16], i & 1);
        sts32(ta + (i >> 1) * 1024 + (i & 1) * 32, tl[i]);
      }
      if (wg < 2) {
        if (pub) {
          bar_sync(8, 384); fence_async();
          if (elect()) {
            for (int i = 0; i < 4; i++) send(i);
            for (int i = 0; i < (rt < 10 ? 3 : 2); i++) bulk_s2g(g_t + ((type * 4 + hg) * 32 + 31 - rt - 11 * i) * 512, sb + T_STG + i * 2048, 2048);
            bulk_commit();
          }
        } else bar_sync(8, 384);
      }
#pragma unroll
      for (int i = 0; i < 4; i++) {
        uint32_t* x = pk + 18 * (i >> 1) + (i & 1);
#pragma unroll
        for (int m = 0; m < 4; m++) { ua[4 * i + m] = fin(q4 < m ? x[4 * m + 4] : x[4 * m], i & 1); x[4 * m + 2] = fin(x[4 * m + 2], i & 1); }
      }
      if (ut) mbar_wait(sb + EMPTY_A, 0);
#pragma unroll
      for (int h = 0; h < 8; h++) {
        const int u = h >> 2, m = h & 3;
        stsm4(sa + h * 1024, ua[8 * u + m], ua[8 * u + 4 + m], pk[18 * u + 4 * m + 2], pk[18 * u + 4 * m + 3]);
      }
      if (wg == 2) bar_arrive(8, 384);
      else if (wg == 1 && w == 0) { bar_sync(9, 256); fence_async(); }
      else bar_arrive(9, 256);
      const uint32_t c0 = clock();
      if (pub && elect()) { bulk_wait0(); red_relaxed(cnt(C_QKV + type * 4 + hg), 1); }
      if (pos >= 0 && type) {
        if (type == 1) {
#pragma unroll
          for (int u = 0; u < 2; u++) {
            uint32_t n[4];
#pragma unroll
            for (int m = 0; m < 4; m++) {
              uint32_t r[2];
#pragma unroll
              for (int i = 0; i < 2; i++) {
                const uint32_t x = ua[8 * u + 4 * i + m], y = pk[18 * u + i + 4 * m + 2];
                r[i] = hfma2(x, x, hfma2(y, y, 0));
              }
              n[m] = hadd2(__byte_perm(r[0], r[1], 0x5410), __byte_perm(r[0], r[1], 0x7632));
            }
            const bool o1 = q4 & 1, o2 = q4 & 2;
            const uint32_t a = hadd2(o1 ? n[1] : n[0], __shfl_xor_sync(0xffffffffu, o1 ? n[0] : n[1], 1));
            const uint32_t c = hadd2(o1 ? n[3] : n[2], __shfl_xor_sync(0xffffffffu, o1 ? n[2] : n[3], 1));
            const uint32_t z0 = __byte_perm(tl[2 * u], tl[2 * u + 1], 0x5410), z1 = __byte_perm(tl[2 * u], tl[2 * u + 1], 0x7632);
            const float2 f = h2f(hadd2(hfma2(z0, z0, hfma2(z1, z1, o2 ? c : a)), __shfl_xor_sync(0xffffffffu, o2 ? a : c, 2)));
            uint32_t m = max(__float_as_uint(fabsf(f.x * (w == 3 ? 0.00390625f : 1024.f))), __float_as_uint(fabsf(f.y * (w >= 2 ? 0.00390625f : 1024.f))));
            m = max(m, __shfl_xor_sync(0xffffffffu, m, 4)); m = max(m, __shfl_xor_sync(0xffffffffu, m, 8)); m = max(m, __shfl_xor_sync(0xffffffffu, m, 16));
            if (ln < 4) st_tag(&g_kn[(hg * 8 + 4 * u + q4) * 128 + pos * 4 + w], m, ep);
          }
        } else {
          auto ab = [](uint32_t x) { return __habs2(*(const __half2*)&x); };
          __half2 m = __hmax2_nan(__hmax2_nan(ab(tl[0]), ab(tl[1])), __hmax2_nan(ab(tl[2]), ab(tl[3])));
#pragma unroll
          for (int j = 0; j < 16; j++) m = __hmax2_nan(m, __hmax2_nan(ab(ua[j]), ab(pk[18 * (j >> 3) + 4 * (j >> 1 & 3) + 2 + (j & 1)])));
          const uint32_t x = *(const uint32_t*)&m, vm = __reduce_max_sync(0xffffffffu, max(x & 0x7FFFu, (x >> 16) & 0x7FFFu));
          if (ln == 0) st_tag(&g_vm[hg * 128 + pos * 4 + w], vm, ep);
        }
      }
      if (wg < 2) {
        if (wg == 1 && w == 1 && b < 128) {
          wait_count(cnt(C_QKV + min(ln, 2) * 4 + (b >> 5)), ep * 11);
          if (ln == 0) mbar_arrive(sb + Q_READY);
          __syncwarp();
          fetch_kv(sb, 15, 4, LAND_HI, 5);
          mbar_wait(sb + STAGED, 0);
          fetch_kv(sb, 11, 1, LAND_HI, 0);
        }
        if (wg == 1 && w == 0) {
#pragma unroll 1
          for (int i = 0; i < 8; i++) {
            while (__all_sync(0xffffffffu, (uint32_t)clock() - c0 < D0 + i * DP)) {}
            if (elect()) {
              send(4 + ((i + 6) & 7));
              if (i == 1) { bulk_commit(); bulk_wait_read(); mbar_arrive(sb + STAGED); }
            }
          }
          if (elect()) bulk_commit();
        }
        const uint32_t* tp0 = tails_ptr(11, tid_v() & 127);
        pinl(tp0);
        if (b < 128) load_q(wg, Q_READY);
        if (wg == 1 && w == 0) {
          if (elect()) { bulk_wait0(); red_relaxed(cnt(C_QKV + 12 + type * 4 + hg), 1); mbar_arrive(sb + PUB); }
        }
        if (b < 128) {
          if (wg == 0) {
            uint32_t tk[5], tv[5];
            tails_ld<1>(tk, tv, 11, tp0);
            __syncwarp();
            tails_st<1>(tk, tv, 11, sb);
          } else if (w >= 2) {
            const uint32_t m = max_tagged((w == 3 ? &g_vm[(b >> 5) * 128] : &g_kn[(b >> 2) * 128]) + ln * 2, ep);
            if (ln == 0) {
              sts32(sb + STATS + (w & 1) * 4, __float_as_uint(w == 3 ? 0.015625f * rcp_a(h2f(m).x) : (sqrt_a(__uint_as_float(m)) * 1.003f + 0.025f) * 16.02f));
              mbar_arrive(sb + HAVE_ST);
            }
            __syncwarp();
          }
        }
      }
    }
    if (b >= 128) {
      float y[2][32];
      const int r0 = (b - 128) * 512, row = r0 + wg * 128 + w * 16 + g;
      const uint32_t* xp = (const uint32_t*)pp.xa + row * 288 + 256 + qd;
#pragma unroll
      for (int j = 0; j < 32; j++) {
        uint32_t z;
        asm("mul.rn.bf16x2 %0, %1, %2;" : "=r"(z) : "r"(xp[((j >> 3) * 8 + (j >> 4) * 48) * 288 + (j & 7) * 4]), "r"(((const uint32_t*)pp.dsk)[256 + (j & 7) * 4 + qd]));
        y[j >> 4][4 * (j & 7) + (j >> 2 & 2)] = __uint_as_float(z << 16); y[j >> 4][4 * (j & 7) + (j >> 2 & 2) + 1] = __uint_as_float(z & 0xFFFF0000u);
      }
      fence_regs(y[0]); fence_regs(y[1]);
      bar_sync(7, 512);
      const uint32_t ep = lds32(sb + EPOCH);
      wait_count(cnt(C_QKV + 12 + lane % 12), ep * 11);
#pragma unroll 2
      for (uint32_t i = (b - 128) * 16 + (tid >> 5); i < 1296; i += 64) {
        const uint32_t r = i / 18 * 8 + (lane & 7), c = i % 18 * 4 + (lane >> 3);
        ((uint4*)g_w)[c * 576 + r] = ((const uint4*)pp.wo)[(r < 512 ? (r >> 4) * 18 + (r & 15) : (r - 512 >> 1) * 18 + 16 + (r & 1)) * 72 + c];
      }
      bar_sync(7, 512);
      if (tid == 0) red_release(cnt(C_W), 1);
      const int wv = __shfl_sync(0xffffffffu, tid >> 5, 0);
      auto load = [&](int i) {
        const uint32_t st = sb + i % 3 * 73728 + wv * 8192, fb = sb + FULL_B + i % 3 * 8;
        if (wv < 9 && elect()) {
          if (wv == 8) mbar_expect(fb, 73728);
          tma2d(st, wv < 8 ? &mp.hl : &mp.cr2 + i / 9, wv < 8 ? r0 + wv * 64 : i % 9 * 64, wv < 8 ? i * 64 : 512, fb);
        }
      };
      wait_count(cnt(C_H + min(lane, 12)), ep * 72);
      fence_async_g();
#pragma unroll 1
      for (int i = -3; i < 18; i++) {
        if (i >= 0) {
          mbar_wait(sb + FULL_B + i % 3 * 8, i / 3 & 1);
          const uint32_t la = ((sb + i % 3 * 73728 + wg * 16384) >> 4) | (1u << 16), lb = ((sb + i % 3 * 73728 + 65536) >> 4) | (1u << 16);
          wfence();
#pragma unroll
          for (int kk = 0; kk < 8; kk++) mmt(y[kk & 1], mkdesc(la + (kk & 1) * 512 + (kk >> 1) * 128, SW128 | 64), mkdesc(lb + (kk >> 1) * 2, SW128 | 64), 1);
          wcommit();
          wwait<1>();
          bar_sync(7, 512);
        }
        if (i && i < 16) load(i < 0 ? i + 3 : i + 2);
      }
      wwait<0>();
      fence_regs(y[0]); fence_regs(y[1]);
      float2* yp = (float2*)pp.out + row * 576 + 256 + qd;
#pragma unroll
      for (int j = 0; j < 32; j++) yp[((j >> 3) * 8 + (j >> 4) * 48) * 576 + (j & 7) * 4] = make_float2(y[j >> 4][4 * (j & 7) + (j >> 2 & 2)], y[j >> 4][4 * (j & 7) + (j >> 2 & 2) + 1]);
      return;
    }

    if (wg >= 2) {
      const int half = wg & 1;
      uint32_t tk[6] = {}, tv[6] = {};
      float acc[80];
      if (!ssm) { mbar_wait(sb + Q_READY, 0); tails_ld<2>(tk, tv, half); }
      else {
#pragma unroll 1
      for (int kb = 0; kb < 9; kb++) {
        const int s = kb & 3;
        mbar_wait(sb + FULL_B + 8 * s, (kb >> 2) & 1);
        const uint32_t la = ((sb + s * B_ST + half * 8192) >> 4) | (1u << 16), lb = ((sb + s * B_ST + 16384) >> 4) | (1u << 16);
        wfence();
#pragma unroll
        for (int kk = 0; kk < 4; kk++) mm160(acc, mkdesc(la + kk * 2, SW128 | 64), mkdesc(lb + kk * 2, SW128 | 64), kk ? 1 : kb);
        wcommit();
        if (kb == 8) { mbar_wait(sb + Q_READY, 0); tails_ld<2>(tk, tv, half); }
        wwait<1>();
        if (kb > 0 && kb < 6) {
          const int sp = (kb - 1) & 3;
          if (lane == 0) mbar_arrive(sb + EMPTY_B + 8 * sp);
          if (w == 0) {
            mbar_wait(sb + EMPTY_B + 8 * sp, (kb - 1) >> 2);
            if (elect()) load_b(kb + 3, sp, half);
          }
        }
      }
      wwait<0>();
      fence_regs(acc);
      bar_sync(6, 256);
      }
      auto fetch_lo = [&]() {
        if (wg == 3 && w == 3) {
          wait_count(cnt(C_QKV + 12 + min(lane, 2) * 4 + (b >> 5)), lds32(sb + EPOCH) * 11);
          fetch_kv(sb, 10, 11, LAND_LO, 11);
        }
      };
      mbar_wait(sb + PUB, 0);
      fetch_lo();
      if (!ssm) {
        tails_st<2>(tk, tv, half, sb);
        check_kv<10, 11, 256>(sb, LAND_LO, FULL_LO); load_q(wg); }
      else {
      const int prow = half * 32 + w * 8 + g;
      const float4* cp = (const float4*)(smem_raw + CONSTS) + prow;
      float4* ag = g_agg + pt * 64 + prow;
      const uint32_t ep = lds32(sb + EPOCH);
      const cf one = {1.f, 0.f};
      auto bu = [&](int i) { return cf{acc[4 * (i >> 1) + (i & 1)], acc[4 * (i >> 1) + 2 + (i & 1)]}; };
      const float4 c0 = cp[0], c1 = cp[64];
      const cf lam = {c0.x, c0.y};
      const cf lx = J == 20 ? lam : one;
      if (J != 20) {
#pragma unroll
        for (int i = 64; i < 80; i++) acc[i] = 0.f;
      }
      fence_regs(acc);
      cf x0 = bu(0), x = bu(24);
#pragma unroll
      for (int i = 1; i < 24; i++) {
        x0 = cfma(lam, x0, bu(i));
        if (i < 16) x = cfma(i < 8 ? lam : lx, x, bu(24 + i));
      }
      x = cfma(cf{c0.z, c0.w}, x0, x);
      cf y = cshfl_up(x, 1); if (qd >= 1) x = cfma(cf{c1.x, c1.y}, y, x);
      y = cshfl_up(x, 2); if (qd >= 2) x = cfma(cf{c1.z, c1.w}, y, x);
      y = cshfl_up(x, 1);
      if (qd == 0) y = cf{0.f, 0.f};
      if (qd == 3 && tt < 12)
        asm volatile("st.relaxed.gpu.global.v4.f32 [%0], {%1, %2, %3, %2};" ::"l"(ag + tt * 576), "f"(x.r), "f"(__uint_as_float(ep)), "f"(x.i) : "memory");
      __syncwarp();
      tails_st<2>(tk, tv, half, sb);
      float4 pre[3];
#pragma unroll
      for (int i = 0; i < 3; i++) {
        const int j = tt - 1 - qd - 4 * i;
        pre[i] = make_float4(0.f, __uint_as_float(ep), 0.f, __uint_as_float(ep));
        if (j >= 0) pre[i] = ld_l2_f4(ag + j * 576);
      }
      check_kv<10, 11, 256>(sb, LAND_LO, FULL_LO);
      const float4 c2 = cp[128], c3 = cp[192], c4 = cp[256];
      cf c = {0.f, 0.f};
#pragma unroll
      for (int i = 2; i >= 0; i--) {
        for (uint32_t it = 0; __any_sync(0xffffffffu, __float_as_uint(pre[i].y) != ep || __float_as_uint(pre[i].w) != ep);) {
          const int j = tt - 1 - qd - 4 * i;
          if (j >= 0) pre[i] = ld_l2_f4(ag + j * 576);
          if (++it > (1u << 21)) __trap();
        }
        c = cfma(cf{c2.z, c2.w}, c, cf{pre[i].x, pre[i].z});
      }
      c = cmul(c, cmul((qd & 1) ? cf{c3.x, c3.y} : one, (qd & 2) ? cf{c3.z, c3.w} : one));
      c.r += __shfl_xor_sync(0xffffffffu, c.r, 1); c.i += __shfl_xor_sync(0xffffffffu, c.i, 1);
      c.r += __shfl_xor_sync(0xffffffffu, c.r, 2); c.i += __shfl_xor_sync(0xffffffffu, c.i, 2);
      cf h[2];
      h[0] = cfma(cmul((qd & 1) ? cf{c1.x, c1.y} : one, (qd & 2) ? cf{c1.z, c1.w} : one), c, y);
      h[1] = cfma(cf{c2.x, c2.y}, h[0], x0);
      load_q(wg);
      const uint32_t a0 = sb + half * 10240 + (w * 8 + g) * 16 * J + qd * 4 * J;
#pragma unroll
      for (int jj = 0; jj < 5; jj++) {
        const int j = jj == 4 ? 2 : (jj >> 1) + 3 * (jj & 1), u = j >= 3;
        if (j < 4 || J == 20) {
          uint32_t xr[4], xi[4];
#pragma unroll
          for (int i = 0; i < 4; i++) {
            const cf p = cfma(lam, h[u], bu(8 * j + 2 * i));
            h[u] = cfma(lam, p, bu(8 * j + 2 * i + 1));
            xr[i] = packbf(fmaf(c4.x, p.r, c4.y * p.i), fmaf(c4.x, h[u].r, c4.y * h[u].i));
            xi[i] = packbf(fmaf(c4.z, p.r, c4.w * p.i), fmaf(c4.z, h[u].r, c4.w * h[u].i));
          }
          sts128(a0 + 16 * j, xr[0], xr[1], xr[2], xr[3]); sts128(a0 + 20480 + 16 * j, xi[0], xi[1], xi[2], xi[3]);
        }
      }
      bar_sync(1 + wg, 128);
      if (t == 0) {
        fence_async();
        const CUtensorMap* m = J == 20 ? &mp.hs20 : &mp.hs16;
        tma2d_store(m, sb + half * 10240, tt * 160, pt * 64 + half * 32);
        tma2d_store(m, sb + 20480 + half * 10240, tt * 160, 576 + pt * 64 + half * 32);
        bulk_commit();
      }
      __syncwarp();
      }
    }
  }

  auto early_w = [&]() {
    if (__shfl_sync(0xffffffffu, tid_v() >> 5 & 3, 0) == 0) {
      const uint32_t b = bid_v();
      mbar_wait(sb + KV_FREE, 0);
      if (elect()) {
        fence_async_g();
        mbar_expect(sb + FULL_W, 82944);
        bulk_g2s(sb + W_OFF, g_w + (b & 7) * 82944, 82944, sb + FULL_W);
        mbar_expect(sb + FULL_O, 49152);
        bulk_g2s(sb, g_o + (b >> 3) * 73728, 49152, sb + FULL_O);
      }
    }
  };
  const uint32_t kv0 = __shfl_sync(0xffffffffu, (sb + KV_OFF + 15 * 10240) >> 4, 0);
  mbar_wait(sb + HAVE_ST, 0);
  __syncwarp();
#pragma unroll 1
  for (int it = 0; it < 3; it++) {
    if (it == 1 && wg >= 2) continue;
    if (it == 1 && wg == 0) {
      const int b = bid_v(), t = tid_v() & 127, lane = t & 31, qd = t & 3;
      const int w = __shfl_sync(0xffffffffu, t >> 5, 0), tt2 = b & 31, d0 = (b >> 5) * 128;
      const CUtensorMap* mc = w ? &mp.cr : &mp.hl;
      int c0 = w ? 0 : tt2 * 64, c1 = w ? d0 : 0;
      auto load_c = [&](int s) {
        if (elect()) {
          if (w == 0) mbar_expect(sb + FULL_C + 8 * s, 24576);
          tma2d(sb + s * C_ST + w * 8192, mc, c0, c1, sb + FULL_C + 8 * s);
        }
        if (w == 0) c1 += 64;
        else if ((c0 += 64) == 576) { c0 = 0; mc++; }
      };
      if (w < 2) {
        if (b < NSSM) mbar_wait(sb + STG_FREE, 0);
        if (w == 0) wait_count(cnt(lane & 2 ? C_W : C_H + (tt2 * 64 + (lane & 1) * 63) / 160), lds32(sb + EPOCH) * (lane & 2 ? 4 : 72));
        fence_async_g();
        load_c(0); load_c(1);
      }
      float acc[64];
#pragma unroll
      for (int j = 0; j < 64; j++) acc[j] = 0.f;
#pragma unroll 1
      for (int i = 0; i < 9; i++) {
#pragma unroll
        for (int s = 0; s < 2; s++) {
          mbar_wait(sb + FULL_C + 8 * s, i & 1);
          const uint32_t la = ((sb + s * C_ST) >> 4) | (1u << 16), lb = ((sb + s * C_ST + 8192) >> 4) | (1u << 16);
          wfence();
#pragma unroll
          for (int kk = 0; kk < 4; kk++) mmt(acc, mkdesc(la + kk * 128, SW128 | 64), mkdesc(lb + kk * 2, SW128 | 64), 1);
          wcommit();
          wwait<0>();
          if (w >= 2 && (i < 8 || s == 0)) bar_arrive(11 + s, 128);
          else {
            bar_sync(11 + s, 128);
            if (i < 8) load_c(s);
            else if (s == 0 && elect()) {
              if (w == 0) { mbar_expect(sb + FULL_C, 17664); bulk_g2s(sb + 18432, pp.dsk + d0, 256, sb + FULL_C); }
              else tma2d(sb, &mp.xs, d0, tt2 * 64, sb + FULL_C);
            }
          }
        }
      }
      fence_regs(acc);
      mbar_wait(sb + FULL_C, 1);
      uint32_t xa = sb + (w * 16 + (lane & 15)) * 272 + (lane >> 4) * 16, da = sb + 18432 + (lane >> 3) * 16, d[4];
      uint32_t a0 = sb + Y_OFF + (w * 16 + (lane >> 2)) * 64 + (qd & 1) * 8 + (((qd >> 1) ^ (lane >> 3)) << 4);
      pin(xa); pin(da); pin(a0);
#pragma unroll
      for (int j = 0; j < 16; j += 2) {
        uint32_t x[4];
        if (!(j & 2)) ldsm4(d, da + j * 16);
        ldsm4(x, xa + j * 16);
#pragma unroll
        for (int i = 0; i < 4; i++) {
          uint32_t y;
          asm("mul.rn.bf16x2 %0, %1, %2;" : "=r"(y) : "r"(x[i]), "r"(d[(j & 2) + (i >> 1)]));
          sts64((a0 ^ (i >> 1) * 32) + j * 2048 + (i & 1) * 512, __float_as_uint(acc[4 * j + 2 * i] + __uint_as_float(y << 16)),
                __float_as_uint(acc[4 * j + 2 * i + 1] + __uint_as_float(y & 0xFFFF0000u)));
        }
      }
      load_q(4);
      bar_sync(1, 128);
      if (t == 0) { fence_async(); tma3d_store(&mp.out, sb + Y_OFF, 0, tt2 * 64, (b >> 5) * 8); bulk_commit(); }
      __syncwarp();
      continue;
    }
    auto duty = [&]() {
      if (it == 2 && (tid_v() & 31) == 0) { bulk_wait_read(); mbar_arrive(sb + KV_FREE); }
      __syncwarp();
    };
    float need[2], vn;
    bool slow;
    {
      const uint4 st = lds128(sb + STATS);
      const int qd = tid_v() & 3;
      float B[2];
      for (uint32_t n = 0;;) {
        const uint32_t bad = lop3<0xFE>(stale<2>(q, st.z), stale<2>(q + 2, st.z), qd ? 0 : stale<2>(q + 4, st.z));
#pragma unroll
        for (int r = 0; r < 2; r++) {
          const float2 a = h2f(q[r]), c = h2f(q[2 + r]), d = h2f(q[4 + r]);
          float x = (a.x * a.x + a.y * a.y) + (c.x * c.x + c.y * c.y) + (d.x * d.x + d.y * d.y);
          x += __shfl_xor_sync(0xffffffffu, x, 1); x += __shfl_xor_sync(0xffffffffu, x, 2);
          B[r] = sqrt_a(x) * __uint_as_float(st.x);
        }
        if (!__any_sync(0xffffffffu, lop3<0xC0>(bad, 1, 0))) break;
        load_q(it == 0 ? wg : it == 1 ? 4 : 4 + wg);
        if (++n > (1u << 21)) __trap();
      }
#pragma unroll
      for (int r = 0; r < 2; r++) {
        const float c0 = fminf(fminf(fmaxf(B[r], 8.f), 12.f), 28.3f - B[r]);
        need[r] = B[r] - c0;
        if (qd == 1) q[4 + r] = packh(c0 * 0.0625f, 0.0625f);
      }
      vn = __uint_as_float(st.y);
      slow = bar_or(1 + wg, 128, !(B[0] <= 20.f && B[1] <= 20.f));
    }
    if (it == 0) {
      if (wg < 2) check_kv<15, 5, 256>(sb, LAND_HI, FULL_HI);
      mbar_wait(sb + FULL_HI, 0);
    }
    const bool hpub = it == 0 && wg >= 2 && blockIdx.x < NSSM;
    auto h_read = [&]() {
      const int b = bid_v(), t = tid_v() & 127, tt = (b % 39) / 3;
      if (t == 0) { bulk_wait0(); mbar_arrive(sb + STG_FREE); fence_async_g(); }
      __syncwarp();
      bar_sync(1 + wg, 128);
      const uint8_t* hp = g_h + ((t >> 6) * 576 + ((b / 39) * 3 + (b % 39) % 3) * 64 + (wg & 1) * 32 + (t >> 1 & 31)) * 4096 + tt * 320 + (t & 1) * 208;
      cp16(sb + SINK, hp); cp16(sb + SINK, hp + (tt == 12 && (t & 1) ? 32 : 96));
    };
    auto h_count = [&]() {
      if (hpub) {
        asm volatile("cp.async.wait_all;" ::: "memory");
        __syncwarp();
        if ((tid_v() & 31) == 0) red_relaxed(cnt(C_H + (bid_v() % 39) / 3), 1);
        __syncwarp();
      }
    };
    uint4 x4; uint2 x2;
    uint8_t *op4, *op2;
    auto finish = [&](const float (&o)[12], float l0, float l1, uint32_t t) {
      const uint32_t b = bid_v(), qd = t & 3, head = b >> 2, ep = lds32(sb + EPOCH);
      const float i0 = rcp_a(l0), i1 = rcp_a(l1);
      uint8_t* op = g_o + ((it * 2 + wg) * 4 + (b & 3)) * 73728u;
      op4 = op + (head * 2048 + (t & 124) * 16 + ((qd - head) & 3) * 16);
      op2 = op + (65536 + (head >> 3) * 2048 + (head & 3) * 16 + (head & 4) * 2 + (t & 124) * 16);
      uint32_t x[6];
#pragma unroll
      for (int j = 0; j < 6; j++) x[j] = packbf(o[2 * j] * (j & 1 ? i1 : i0), o[2 * j + 1] * (j & 1 ? i1 : i0));
      const bool lo = qd >= (head & 3);
      x4 = make_uint4(tag(lo ? x[0] : x[2], ep), lo ? x[1] : x[3], tag(lo ? x[2] : x[0], ep), lo ? x[3] : x[1]);
      x2 = make_uint2(tag(x[4], ep), x[5]);
    };
    auto put = [&](uint32_t lane, bool on) {
      asm volatile("{\n.reg .pred p, q, r;\nsetp.ne.u32 r, %10, 0;\nsetp.eq.and.u32 p, %8, 2, r;\nsetp.eq.and.u32 q, %9, 0, r;\n"
                   "@r st.global.v4.u32 [%0], {%1, %2, %3, %4};\n@p st.global.v2.u32 [%5], {%6, %7};\n@q red.relaxed.gpu.global.add.u32 [%11], 1;\n}"
                   ::"l"(op4), "r"(x4.x), "r"(x4.y), "r"(x4.z), "r"(x4.w), "l"(op2), "r"(x2.x), "r"(x2.y), "r"(lane & 3), "r"((lane & 31) | (it ^ 2)), "r"((uint32_t)on),
                   "l"(cnt(C_O + wg * 4 + (bid_v() & 3))) : "memory");
    };
    bool done = false;
    const bool fast = !slow;
    if (fast) {
      uint32_t c2 = 0x47B147B1u + q[6];
      asm volatile("" : "+r"(c2));
      fence_regs(q);
      uint32_t k = kv0 | (128u << 16), kt = kv0 + 512, v = (kv0 + 256) | (8u << 16);
      uint32_t sa[16], sc[16], pa[16], pc[16], a[6], a1[6];
#pragma unroll
      for (int i = 0; i < 6; i++) a[i] = a1[i] = 0;
      const bool hsp = it == 0 && wg >= 2;
      int n = it == 0 ? (hsp ? 1 : 4) : it == 1 ? NEXP : 8, hf = hsp ? -1 : 0;
      if (it == 2 && wg == 0) {
        n = 16 - NEXP; k -= 640 * NEXP; kt -= 640 * NEXP; v -= 640 * NEXP;
        mbar_wait(sb + PART, 0);
        const uint32_t t = tid_v() & 127, pb = sb + EXCH;
        const uint2 x = lds64(pb + t * 8), y = lds64(pb + 1024 + t * 8), z = lds64(pb + 2048 + (t >> 2) * 16 + (t & 1) * 8);
        a1[0] = x.x; a1[1] = x.y; a1[2] = y.x; a1[3] = y.y; a1[4] = z.x; a1[5] = z.y;
        hf = 1;
        duty();
      }
      uint32_t pad[PAD];
      fence_regs(a);
      wfence(); qk_h(sa, q, k, kt, 0); wcommit();
#pragma unroll
      for (int i = 0; i < PAD; i++) asm volatile("ld.volatile.shared.b32 %0, [%1];" : "=r"(pad[i]) : "r"(sb + ZERO) : "memory");
      fence_regs(need);
#pragma unroll
      for (int r = 0; r < 2; r++) { const float z = need[r]; need[r] = fmaxf(z > 0.45f ? 128.f * fmaxf(1.f, (0.2404f * z - 0.7031f) * z + 1.01f) : 0.f, vn); }
      fence_regs(need);
      wwait<0>(); fence_regs(sa);
#pragma unroll 1
      for (;; hf++) {
#pragma unroll 1
        do {
          wfence(); qk_h(sc, q, k, kt, 64); wcommit();
          exp_chunk(pa, sa, c2);
          fence_regs(pa); wfence(); pv_h(a, pa, v, 0); wcommit();
          qk_h(sa, q, k, kt, -640); wcommit();
          wwait<2>(); fence_regs(sc);
          exp_chunk(pc, sc, c2);
          fence_regs(pc); wfence(); pv_h(a, pc, v, 64); wcommit();
          k -= 640; kt -= 640; v -= 640;
          wwait<1>(); fence_regs(sa);
        } while (--n);
        wwait<0>(); fence_regs(a);
        if (it == 1) break;
        if (hf < 0) { if (hpub) h_read(); n = 3; }
        else if (hf == 0) {
#pragma unroll
          for (int i = 0; i < 6; i++) { a1[i] = a[i]; a[i] = 0; }
          n = it == 0 ? 12 : wg == 2 ? 2 : 8;
          duty();
          h_count();
          mbar_wait(sb + FULL_LO, 0);
        } else if (hf == 1 && it == 2 && wg == 2) {
          early_w();
          n = 6;
        } else break;
      }
      uint32_t t = tid_v();
      if (it == 1) {
        t &= 127;
        const uint32_t pb = sb + EXCH;
        if (bid_v() < NSSM) mbar_wait(sb + STG_FREE, 0);
        sts64(pb + t * 8, a[0], a[1]); sts64(pb + 1024 + t * 8, a[2], a[3]);
        if (t & 2) sts64(pb + 2048 + (t >> 2) * 16 + (t & 1) * 8, a[4], a[5]);
        __syncwarp();
        if ((t & 31) == 0) mbar_arrive(sb + PART);
        __syncwarp();
      } else {
        float o[12], m[4];
#pragma unroll
        for (int i = 0; i < 6; i++) { const float2 x = h2f(a[i]), y = h2f(a1[i]); o[2 * i] = x.x + y.x; o[2 * i + 1] = x.y + y.y; }
        const float l0 = __shfl_sync(0xffffffffu, o[8], t | 3), l1 = __shfl_sync(0xffffffffu, o[10], t | 3);
#pragma unroll
        for (int i = 0; i < 4; i++) m[i] = fabsf(o[i]) + fabsf(o[4 + i]) + (t & 2 ? fabsf(o[8 + i]) : 0.f);
        finish(o, l0, l1, t);
        done = __all_sync(0xffffffffu, (m[0] + m[1]) + (m[2] + m[3]) < INFINITY && l0 >= need[0] && l1 >= need[1]);
        put(t, done);
#pragma unroll
      for (int i = 0; i < PAD; i++) asm volatile("{\n.reg .pred p;\nsetp.ne.u32 p, %0, 0;\n@p trap;\n}" ::"r"(pad[i]));
        slow = bar_or(1 + wg, 128, !done);
      }
    }
    if (it == 1) { load_q(4 + wg); continue; }
    if (slow) {
      const int t = tid_v() & 127;
      const bool strm = fast && it == 2;
      if ((t & 3) == 1) q[4] = q[5] = 0;
      fence_regs(q);
      if (!fast && hpub) { h_read(); h_count(); }
      mbar_wait(sb + FULL_LO, 0);
      if (strm) mbar_wait(sb + KV_FREE, 0);
      if (strm && __shfl_sync(0xffffffffu, t >> 5, 0) == 0)
        for (uint32_t n = 0; __any_sync(0xffffffffu, t == 0 && atomicCAS((uint32_t*)(smem_raw + XLOCK), 0u, 1u)); __nanosleep(200))
          if (++n > (1u << 21)) __trap();
      float m0 = -INFINITY, m1 = -INFINITY, o[12] = {};
#pragma unroll 1
      for (int c = 0; c < 32; c++) {
        uint32_t base = kv0 - 640 * (c >> 1);
        if (strm && c < 16) {
          base = __shfl_sync(0xffffffffu, (sb + X_OFF) >> 4, 0);
          if (!(c & 1)) {
            bar_sync(1 + wg, 128);
            const int kc = 15 - (c >> 1);
            if (t == 0) { mbar_expect(sb + FULL_X, 8192); bulk_g2s(sb + X_OFF, g_kv + (bid_v() >> 2) * 131072 + kc * 8192, 8192, sb + FULL_X); }
            const uint32_t* tp = tails_ptr(kc, t);
            sts128(sb + X_OFF + 8192 + t * 16, ld_l2(tp), k_const(t), ld_l2(tp + 65536), 0x00003C00u);
            fence_async();
            bar_sync(1 + wg, 128);
            mbar_wait(sb + FULL_X, (c >> 1) & 1);
          }
        }
        base += (c & 1) * 64;
        float s[32]; uint32_t p[16];
        wfence();
        qk64f(s, q[0], q[1], q[2], q[3], mkdesc(base | (128u << 16), 8), 0); qk64f(s, q[4], q[5], q[6], q[7], mkdesc(base + 512, 8), 1);
        wcommit(); wwait<0>(); fence_regs(s); fence_regs(o);
#pragma unroll
        for (int j = 0; j < 20; j++) s[j] *= 512.f;
        float a0 = m0, a1 = m1;
#pragma unroll
        for (int j = 0; j < 8; j++) { a0 = fmaxf(a0, fmaxf(s[4 * j], s[4 * j + 1])); a1 = fmaxf(a1, fmaxf(s[4 * j + 2], s[4 * j + 3])); }
        a0 = fmaxf(a0, __shfl_xor_sync(0xffffffffu, a0, 1)); a0 = fmaxf(a0, __shfl_xor_sync(0xffffffffu, a0, 2));
        a1 = fmaxf(a1, __shfl_xor_sync(0xffffffffu, a1, 1)); a1 = fmaxf(a1, __shfl_xor_sync(0xffffffffu, a1, 2));
        const float c0 = ex2(m0 - a0), c1 = ex2(m1 - a1);
        m0 = a0; m1 = a1;
#pragma unroll
        for (int j = 0; j < 3; j++) { o[4 * j] *= c0; o[4 * j + 1] *= c0; o[4 * j + 2] *= c1; o[4 * j + 3] *= c1; }
#pragma unroll
        for (int j = 0; j < 8; j++) { p[2 * j] = packh(ex2(s[4 * j] - m0), ex2(s[4 * j + 1] - m0)); p[2 * j + 1] = packh(ex2(s[4 * j + 2] - m1), ex2(s[4 * j + 3] - m1)); }
        fence_regs(p); fence_regs(o);
        wfence();
#pragma unroll
        for (int kk = 0; kk < 4; kk++) pv24f(o, p[4 * kk], p[4 * kk + 1], p[4 * kk + 2], p[4 * kk + 3], mkdesc(((base + 256) | (8u << 16)) + kk * 16, 128), 1);
        wcommit(); wwait<0>(); fence_regs(o);
      }
      if (strm) { bar_sync(1 + wg, 128); if (t == 0) atomicExch((uint32_t*)(smem_raw + XLOCK), 0u); }
      if (!fast) { duty(); if (it == 2 && wg == 2) early_w(); }
      __syncwarp();
      finish(o, __shfl_sync(0xffffffffu, o[8], t | 3), __shfl_sync(0xffffffffu, o[10], t | 3), t);
      put(t, !done);
    }
    if (it == 0 && wg) load_q(wg == 1 ? 4 : 4 + wg);
    __syncwarp();
  }

  const int w3 = 0x3201 >> (__shfl_sync(0xffffffffu, tid_v() >> 7, 0) * 4) & 3;
  const int b = bid_v(), t = (tid_v() & 127) + ((q[0] | q[1] | q[2] | q[3] | q[4] | q[5]) & q[6]), s = w3 != 3, u = s * 16 + (b >> 3);
  const uint32_t ep = lds32(sb + EPOCH);
  if (w3 == 2) bar_arrive(5, 256);
  const uint32_t st = sb + 24576 + s * 18432;
  uint32_t a0 = st + ((t >> 5) * 16 + (t >> 2 & 7)) * 288 + (t & 3) * 8, a1 = sb + t * 16;
  const uint32_t* co = cnt(C_O + (b >> 3));
  float acc[36];
  int r = s ? 2 - w3 : -1;
  pin(a0); pin(a1);
#pragma unroll 1
  do {
    const int h = r < 0 ? 2 : r;
    const uint8_t* gp = g_o + u * 73728 + h * 24576 + t * 16;
    const uint32_t lw = (((sb + W_OFF) >> 4) | (8u << 16)) + h * 192;
    pinl(gp);
    if (w3 == 2) wait_count(co, ep * 128 - THR);
    if (w3 < 2) bar_sync(13 + w3, 256);
    if (!s && r == 0) mbar_wait(sb + FULL_O, 0);
    uint4 f[12];
    if (s || r < 0) {
#pragma unroll
      for (int j = 0; j < 12; j++) f[j] = ld_l2_u4(gp + j * 2048);
      if (w3 == 1 || w3 == 2) bar_arrive(12 + w3, 256);
    } else {
#pragma unroll
      for (int j = 0; j < 12; j++) f[j] = lds128(a1 + h * 24576 + j * 2048);
    }
    mbar_wait(sb + FULL_W, 0);
    for (uint32_t n = 0;;) {
      uint32_t m[12];
#pragma unroll
      for (int j = 0; j < 12; j++) m[j] = lop3<0x7E>(f[j].x, f[j].z, ep);
#pragma unroll
      for (int j = 0; j < 4; j++) m[j] = lop3<0xFE>(m[j], m[j + 4], m[j + 8]);
      if (!__any_sync(0xffffffffu, lop3<0xA8>(lop3<0xFE>(m[0], m[1], m[2]), m[3], 1))) break;
#pragma unroll
      for (int j = 0; j < 12; j++)
        asm volatile("{\n.reg .pred p;\n.reg .u32 m;\nlop3.b32 m, %0, %2, %5, 0x7E;\nand.b32 m, m, 1;\nsetp.ne.u32 p, m, 0;\n"
                     "@p ld.relaxed.gpu.global.v4.u32 {%0, %1, %2, %3}, [%4];\n}\n"
                     : "+r"(f[j].x), "+r"(f[j].y), "+r"(f[j].z), "+r"(f[j].w) : "l"(gp + j * 2048), "r"(ep) : "memory");
      if (++n > (1u << 21)) __trap();
    }
    if (!s && r == 0) bar_sync(5, 256);
    if (!s && r >= 0) bar_arrive(r ? 6 : 15, 256);
    wfence();
#pragma unroll
    for (int j = 0; j < 12; j++) rsb(acc, f[j].x, f[j].y, f[j].z, f[j].w, mkdesc(lw + j * 16, 576), j || (!s && r >= 0));
    wcommit();
    wwait<0>();
    fence_regs(acc);
  } while (!s && ++r < 2);
  if (w3 < 2) {
    bar_sync(9 + w3, 256);
#pragma unroll
    for (int j = 0; j < 9; j++) {
      const uint4 y = lds128(a1 + j * 2048);
      acc[4 * j] += __uint_as_float(y.x); acc[4 * j + 1] += __uint_as_float(y.y); acc[4 * j + 2] += __uint_as_float(y.z); acc[4 * j + 3] += __uint_as_float(y.w);
    }
  }
  if (w3 == 1 || w3 == 2) {
    if (w3 == 2) bar_sync(15, 256);
#pragma unroll
    for (int j = 0; j < 9; j++) sts128(a1 + j * 2048, __float_as_uint(acc[4 * j]), __float_as_uint(acc[4 * j + 1]), __float_as_uint(acc[4 * j + 2]), __float_as_uint(acc[4 * j + 3]));
    bar_arrive(8 + w3, 256);
    return;
  }
  if (w3) bar_sync(4, 128); else bar_sync(6, 256);
#pragma unroll
  for (int j = 0; j < 18; j++) {
    const uint32_t x = packbf(acc[2 * j], acc[2 * j + 1]);
    sts64(a0 + (j >> 1) * 32 + (j & 1) * 2304, x << 16, x & 0xFFFF0000u);
  }
  bar_sync(1 + w3, 128);
  if (t == 0) { fence_async(); tma2d_store(&mp.out2, st, 576 + (b & 7) * 72, (u % 11 * 3 + u / 11) * 64); bulk_commit(); bulk_wait_read(); }
  __syncwarp();
}
typedef CUresult (*EncodeFn)(CUtensorMap*, CUtensorMapDataType, cuuint32_t, void*, const cuuint64_t*, const cuuint64_t*, const cuuint32_t*,
                             const cuuint32_t*, CUtensorMapInterleave, CUtensorMapSwizzle, CUtensorMapL2promotion, CUtensorMapFloatOOBfill);
struct Dims { cuuint64_t n[5]; cuuint64_t st[4]; cuuint32_t box[5]; };
CUtensorMap make_map(EncodeFn enc, const void* p, int rank, Dims d, bool u32, int swz) {
  CUtensorMap m;
  cuuint32_t es[5] = {1, 1, 1, 1, 1};
  CUresult r = enc(&m, u32 ? CU_TENSOR_MAP_DATA_TYPE_UINT32 : CU_TENSOR_MAP_DATA_TYPE_BFLOAT16, rank, (void*)p, d.n, d.st, d.box, es,
      CU_TENSOR_MAP_INTERLEAVE_NONE, swz == 1 ? CU_TENSOR_MAP_SWIZZLE_128B : swz == 2 ? CU_TENSOR_MAP_SWIZZLE_64B : swz == 3 ? CU_TENSOR_MAP_SWIZZLE_32B : CU_TENSOR_MAP_SWIZZLE_NONE,
      CU_TENSOR_MAP_L2_PROMOTION_L2_128B, CU_TENSOR_MAP_FLOAT_OOB_FILL_NONE);
  (void)r;
  return m;
}
}

extern "C" void kernel_launch(void* const* d_in, const int* in_sizes, int n_in, void* d_out, int out_size) {
  (void)in_sizes; (void)n_in; (void)out_size;
  const __nv_bfloat16* const* in = (const __nv_bfloat16* const*)d_in;
  void* fn = nullptr;
  cudaDriverEntryPointQueryResult qr;
  cudaGetDriverEntryPoint("cuTensorMapEncodeTiled", &fn, cudaEnableDefault, &qr);
  EncodeFn enc = (EncodeFn)fn;
  void *pq, *pkv, *ph;
  cudaGetSymbolAddress(&pq, g_q); cudaGetSymbolAddress(&pkv, g_kv); cudaGetSymbolAddress(&ph, g_h);
  Maps mp;
  mp.xb = make_map(enc, in[9], 3, {{576, 2048, 1}, {1152, 1152 * 2048}, {64, 192, 1}}, false, true);
  mp.w = make_map(enc, in[10], 3, {{64, 576, 27}, {3456, 128}, {64, 64, 3}}, false, true);
  mp.q = make_map(enc, pq, 3, {{512, 32, 32}, {65536, 2048}, {256, 4, 1}}, true, false);
  mp.kv = make_map(enc, pkv, 3, {{512, 32, 64}, {131072, 2048}, {256, 4, 1}}, true, false);
  const bool swp = in[4] < in[3];
  mp.bb = make_map(enc, in[swp ? 4 : 3], 4, {{576, 8, 2, 72}, {1152, (cuuint64_t)((swp ? in[3] - in[4] : in[4] - in[3]) * 2), 9216}, {64, 8, 2, 8}}, false, true);
  mp.xa20 = make_map(enc, in[0], 5, {{576, 2, 4, 20, 12}, {1152, 40 * 1152, 2304, 160 * 1152}, {64, 2, 4, 20, 1}}, false, true);
  mp.xa16 = make_map(enc, in[0], 5, {{576, 2, 4, 16, 16}, {1152, 32 * 1152, 2304, 128 * 1152}, {64, 2, 4, 16, 1}}, false, true);
  mp.hs20 = make_map(enc, ph, 2, {{2048, 1152}, {4096}, {160, 32}}, false, false);
  mp.hs16 = make_map(enc, ph, 2, {{2048, 1152}, {4096}, {128, 32}}, false, false);
  mp.hl = make_map(enc, ph, 2, {{2048, 1152}, {4096}, {64, 64}}, false, true);
  mp.cr = make_map(enc, in[5], 2, {{576, 576}, {1152}, {64, 128}}, false, true);
  mp.ci = make_map(enc, in[6], 2, {{576, 576}, {1152}, {64, 128}}, false, true);
  mp.cr2 = make_map(enc, in[5], 2, {{576, 576}, {1152}, {64, 64}}, false, true);
  mp.ci2 = make_map(enc, in[6], 2, {{576, 576}, {1152}, {64, 64}}, false, true);
  mp.xs = make_map(enc, in[0], 2, {{576, 2048}, {1152}, {136, 64}}, false, false);
  mp.out2 = make_map(enc, d_out, 2, {{1152, 2048}, {4608}, {72, 64}}, true, 0);
  mp.out = make_map(enc, d_out, 3, {{16, 2048, 72}, {4608, 64}, {16, 64, 8}}, true, 2);
  cudaFuncSetAttribute(k_fused, cudaFuncAttributeMaxDynamicSharedMemorySize, SMEM);
  const Ptrs pp = {in[0], in[1], in[2], in[3], in[4], in[5], in[6], in[7], in[8], in[9], in[10], in[11], (float*)d_out};
  k_fused<<<NCTA, 512, SMEM, cudaStreamPerThread>>>(mp, pp);
}
```
